```python
import torch

def _softmax(x, axis=-1):
    return torch.softmax(x, dim=axis)
def _gelu(x):
    return torch.nn.functional.gelu(x, approximate="tanh")
def _silu(x):
    return torch.nn.functional.silu(x)
def _sigmoid(x):
    return torch.sigmoid(x)
def _layernorm(x, axis=-1, eps=1e-5):
    m = x.mean(dim=axis, keepdim=True)
    v = x.var(dim=axis, keepdim=True, unbiased=False)
    return (x - m) / torch.sqrt(v + eps)
def _scatter_add(tgt, idx, src, axis=0):
    return tgt.clone().index_add_(axis, idx, src)
def _segment_sum(src, seg, n):
    out = torch.zeros((n,) + src.shape[1:], dtype=src.dtype)
    return out.index_add_(0, seg, src)
def _pad(x, pw):
    flat = tuple(v for pair in reversed(pw) for v in pair)
    return torch.nn.functional.pad(x, flat)

kernel_name = 'gated_mix__grouped_kv_mqa__ssm_conv_s4__prompt'

def setup_inputs():

    _w = (lambda a: (lambda t: t.to(torch.bfloat16) if t.is_floating_point() else t)(torch.as_tensor(a)))
    def _A_setup():
        B, S, D, H = 1, 2048, 448, 16
        Dh = D // H
        return {
            "x": _w((lambda *s: torch.randn(*s, dtype=torch.bfloat16) * 0.05)(B, S, D)),
            "wq": _w((lambda *s: torch.randn(*s, dtype=torch.bfloat16) * 1.6)(D, H * Dh)),
            "wk": _w((lambda *s: torch.randn(*s, dtype=torch.bfloat16) * 1.6)(D, Dh)),
            "wv": _w((lambda *s: torch.randn(*s, dtype=torch.bfloat16) * 0.05)(D, Dh)),
            "wo": _w((lambda *s: torch.randn(*s, dtype=torch.bfloat16) * 0.05)(H * Dh, D)),
        }
    _A_in = _A_setup()

    def _B_setup():
        B, L, D, N = 1, 2048, 448, 256
        A_re = -(lambda _x: torch.exp(torch.as_tensor(_x)))((lambda *s: torch.randn(*s, dtype=torch.bfloat16) * 3.2)(D, N))
        A_im = torch.pi * (lambda *s: torch.randn(*s, dtype=torch.bfloat16) * 0.05)(D, N)
        B_re = (lambda *s: torch.randn(*s, dtype=torch.bfloat16) * 0.2)(D, N)
        B_im = (lambda *s: torch.randn(*s, dtype=torch.bfloat16) * 0.2)(D, N)
        C_re = (lambda *s: torch.randn(*s, dtype=torch.bfloat16) * 0.2)(D, N)
        C_im = (lambda *s: torch.randn(*s, dtype=torch.bfloat16) * 0.2)(D, N)
        log_dt = (lambda *s: torch.randn(*s, dtype=torch.bfloat16) * 0.05)(D) * 0.5 - 4.0
        Dskip = (lambda *s: torch.randn(*s, dtype=torch.bfloat16) * 0.1)(D)
        return {
            "u": _w((lambda *s: torch.randn(*s, dtype=torch.bfloat16) * 0.05)(B, L, D)),
            "A_re": _w(A_re),
            "A_im": _w(A_im),
            "B_re": _w(B_re),
            "B_im": _w(B_im),
            "C_re": _w(C_re),
            "C_im": _w(C_im),
            "log_dt": _w(log_dt),
            "Dskip": _w(Dskip),
        }
    _B_in = _B_setup()

    return {
        "A_x": _A_in["x"],
        "A_wq": _A_in["wq"],
        "A_wk": _A_in["wk"],
        "A_wv": _A_in["wv"],
        "A_wo": _A_in["wo"],
        "B_u": _B_in["u"],
        "B_A_re": _B_in["A_re"],
        "B_A_im": _B_in["A_im"],
        "B_B_re": _B_in["B_re"],
        "B_B_im": _B_in["B_im"],
        "B_C_re": _B_in["C_re"],
        "B_C_im": _B_in["C_im"],
        "B_log_dt": _B_in["log_dt"],
        "B_Dskip": _B_in["Dskip"],
        "gate_w": _w((lambda *s: torch.randn(*s, dtype=torch.bfloat16) * 0.05)(448) * 16.0),
    }

def reference(A_x, A_wq, A_wk, A_wv, A_wo, B_u, B_A_re, B_A_im, B_B_re, B_B_im, B_C_re, B_C_im, B_log_dt, B_Dskip, gate_w):
    def _A_ref(x, wq, wk, wv, wo):
        B, S, D = x.shape
        H = 16
        Dh = D // H
        q = (lambda x, *d: x.permute(*d))((x @ wq).reshape(B, S, H, Dh), 0, 2, 1, 3)
        k = x @ wk
        v = x @ wv
        scores = torch.einsum("bhqd,bkd->bhqk", q, k) * (Dh ** -0.5)
        p = _softmax(scores, axis=-1)
        o = torch.einsum("bhqk,bkd->bhqd", p, v)
        return (lambda x, *d: x.permute(*d))(o, 0, 2, 1, 3).reshape(B, S, H * Dh) @ wo

    def _B_ref(u, A_re, A_im, B_re, B_im, C_re, C_im, log_dt, Dskip):
        Bsz, L, D = u.shape
        dt = torch.exp(log_dt)[:, None]
        A = A_re + 1j * A_im
        Bc = B_re + 1j * B_im
        Cc = C_re + 1j * C_im
        logdA = dt * A
        dB = dt * Bc
        l = (lambda x, dt: x.to(dt))(torch.arange(L), A_re.dtype)
        P = torch.exp(logdA[:, :, None] * l[None, None, :])
        K = torch.einsum("dn,dnl,dn->dl", Cc, P, dB).real
        L2 = 2 * L
        Kp = _pad(K, ((0, 0), (0, L)))
        up = (lambda x, *d: x.permute(*d))(u, 0, 2, 1)
        up = _pad(up, ((0, 0), (0, 0), (0, L)))
        Kf = (lambda x, axes=(-2,-1): torch.fft.rfft2(x.float(), dim=axes))(Kp[:, None, :], axes=(-2, -1))
        Uf = (lambda x, axes=(-2,-1): torch.fft.rfft2(x.float(), dim=axes))(up[:, :, None, :], axes=(-2, -1))
        Yf = Uf * Kf[None, :, :, :]
        y = (lambda x, s, axes=(-2,-1): torch.fft.irfft2(x, s=s, dim=axes).to(torch.bfloat16))(Yf, (1, L2), axes=(-2, -1))[:, :, 0, :L]
        y = (lambda x, *d: x.permute(*d))(y, 0, 2, 1) + u * Dskip[None, None, :]
        return y

    x = A_x
    g = _sigmoid((x * gate_w).sum(-1, keepdims=True))
    a = _A_ref(x, A_wq, A_wk, A_wv, A_wo)
    b = _B_ref(x, B_A_re, B_A_im, B_B_re, B_B_im, B_C_re, B_C_im, B_log_dt, B_Dskip)
    return g * a + (1 - g) * b
```

```cpp
#include <cuda_runtime.h>
#include <cuda_bf16.h>
#include <cuda_fp16.h>
#include <cuda.h>
#include <stdint.h>

namespace {

constexpr int SEQ = 2048, DM = 448, NST = 256;
constexpr int NMAIN = 128, NCTA = 132;
constexpr int NHAND = 48, CH_HAND = DM - NHAND;
constexpr int KP_STRIDE = 648;
#define EMASK 0xDADAu
constexpr uint32_t EMU_MASK = EMASK;
constexpr float SCORE_BOUND = 96.0f;
#define KG_UNROLL 8
#define KG_STR2(x) #x
#define KG_STR(x) KG_STR2(x)
#define KG_PRAGMA KG_STR(unroll KG_UNROLL)
#define AT_UNROLL 4
#define AT_PRAGMA KG_STR(unroll AT_UNROLL)
#define AT_SHAPE 2
#define POLL_NS 100

constexpr uint32_t SM_RING = 0;
constexpr uint32_t SM_QS   = 65536;
constexpr uint32_t SM_B2   = 73728;
constexpr uint32_t SM_STG  = 88064;
constexpr uint32_t SM_U    = 202752;
constexpr uint32_t SM_WO4  = 57344;
constexpr uint32_t SM_WO   = 86016;
constexpr uint32_t SM_O    = 200704;
constexpr uint32_t SM_MISC = 229376;
constexpr uint32_t SM_TOTAL = 232448;
constexpr uint32_t BOX = 28672, U_LBO = 1184, U_SIZE = 4736;
constexpr uint32_t ST_PT = 3456, ST_T3 = 5696, ST_X = 6272, ST_B3 = 17792, ST_X2 = 22912;
constexpr uint32_t B_FULLA = 0, B_FULLKV = 32, B_U = 64, B_XA = 96, B_WO0 = 104, B_WOA = 112, B_WOB = 120, B_WO4 = 128, B_ORECV = 136,
                   B_QSENT = 144, B_PEER = 160, B_DONE = 168, B_YRDY = 176,
                   B_QRDY = 184,
                   B_FREEA = 192, B_SXT = 216, B_SQKV = 224, B_SKP = 232, B_GEN = 296, B_PART = 304,
                   B_SY = 240,
                   B_OST = 248, B_EMPTY = 256, B_OW = 312  ,
                   B_B2 = 288, B_SQ = 344  ,
                   B_T3 = 352  , B_X2 = 376  , M_ISC = 400, M_NORM = 512;
constexpr int C_XT = 0, C_QKV = 32, C_Y = 64, C_KP = 128, C_Q = C_KP + NHAND * 8;
constexpr unsigned N_XT = NMAIN, N_QKV = NMAIN, N_Y = NMAIN + 16, N_KP = 2, N_Q = 4;

struct __align__(1024) Scratch {
  uint32_t Q[NMAIN * 4096];
  uint32_t KV[16 * 4096];
  uint16_t xT[DM * SEQ];
  uint16_t bT[DM * SEQ];
  uint16_t gate[SEQ];
  float norm[512];
  float Kp[NHAND * 2 * KP_STRIDE];
  unsigned cnt[C_Q + 32 * 8];
  unsigned epoch[NCTA];
};
__device__ Scratch gs_;
#define TS(i)
#define TG(i)
#define TL(i)
#define TDUMP()
#define TT(tile, k)

struct Params {
  const uint16_t *are, *aim, *bre, *bim, *cre, *cim, *ldt;
  Scratch* g;
  const uint16_t *wk, *wv, *gw, *dsk;
  uint16_t* out;
};

__device__ __forceinline__ void mma_q112(float (&d)[56], uint32_t a0, uint32_t a1, uint32_t a2, uint32_t a3, uint64_t db, int acc) {
  asm volatile("{\n.reg .pred p;\nsetp.ne.b32 p, %61, 0;\n"
      "wgmma.mma_async.sync.aligned.m64n112k16.f32.bf16.bf16 "
      "{%0,%1,%2,%3,%4,%5,%6,%7,%8,%9,%10,%11,%12,%13,%14,%15,%16,%17,%18,%19,%20,%21,%22,%23,%24,%25,%26,%27,%28,%29,%30,%31,%32,%33,%34,%35,%36,%37,%38,%39,%40,%41,%42,%43,%44,%45,%46,%47,%48,%49,%50,%51,%52,%53,%54,%55}, "
      "{%56,%57,%58,%59}, %60, p, 1, 1, 1;\n}\n"
      : "+f"(d[0]), "+f"(d[1]), "+f"(d[2]), "+f"(d[3]), "+f"(d[4]), "+f"(d[5]), "+f"(d[6]), "+f"(d[7]),
        "+f"(d[8]), "+f"(d[9]), "+f"(d[10]), "+f"(d[11]), "+f"(d[12]), "+f"(d[13]), "+f"(d[14]), "+f"(d[15]),
        "+f"(d[16]), "+f"(d[17]), "+f"(d[18]), "+f"(d[19]), "+f"(d[20]), "+f"(d[21]), "+f"(d[22]), "+f"(d[23]),
        "+f"(d[24]), "+f"(d[25]), "+f"(d[26]), "+f"(d[27]), "+f"(d[28]), "+f"(d[29]), "+f"(d[30]), "+f"(d[31]),
        "+f"(d[32]), "+f"(d[33]), "+f"(d[34]), "+f"(d[35]), "+f"(d[36]), "+f"(d[37]), "+f"(d[38]), "+f"(d[39]),
        "+f"(d[40]), "+f"(d[41]), "+f"(d[42]), "+f"(d[43]), "+f"(d[44]), "+f"(d[45]), "+f"(d[46]), "+f"(d[47]),
        "+f"(d[48]), "+f"(d[49]), "+f"(d[50]), "+f"(d[51]), "+f"(d[52]), "+f"(d[53]), "+f"(d[54]), "+f"(d[55])
      : "r"(a0), "r"(a1), "r"(a2), "r"(a3), "l"(db), "r"(acc));
}
__device__ __forceinline__ void mma_rs64_z(float (&d)[32], uint32_t a0, uint32_t a1, uint32_t a2, uint32_t a3, uint64_t db) {
  asm volatile("{\n.reg .pred p;\nsetp.ne.b32 p, 0, 0;\n"
      "wgmma.mma_async.sync.aligned.m64n64k16.f32.bf16.bf16 "
      "{%0,%1,%2,%3,%4,%5,%6,%7,%8,%9,%10,%11,%12,%13,%14,%15,%16,%17,%18,%19,%20,%21,%22,%23,%24,%25,%26,%27,%28,%29,%30,%31}, "
      "{%32,%33,%34,%35}, %36, p, 1, 1, 0;\n}\n"
      : "=f"(d[0]), "=f"(d[1]), "=f"(d[2]), "=f"(d[3]), "=f"(d[4]), "=f"(d[5]), "=f"(d[6]), "=f"(d[7]),
        "=f"(d[8]), "=f"(d[9]), "=f"(d[10]), "=f"(d[11]), "=f"(d[12]), "=f"(d[13]), "=f"(d[14]), "=f"(d[15]),
        "=f"(d[16]), "=f"(d[17]), "=f"(d[18]), "=f"(d[19]), "=f"(d[20]), "=f"(d[21]), "=f"(d[22]), "=f"(d[23]),
        "=f"(d[24]), "=f"(d[25]), "=f"(d[26]), "=f"(d[27]), "=f"(d[28]), "=f"(d[29]), "=f"(d[30]), "=f"(d[31])
      : "r"(a0), "r"(a1), "r"(a2), "r"(a3), "l"(db));
}
__device__ __forceinline__ void mma_ss128_z(float (&d)[64], uint64_t da, uint64_t db) {
  asm volatile("{\n.reg .pred p;\nsetp.ne.b32 p, 0, 0;\n"
      "wgmma.mma_async.sync.aligned.m64n128k16.f32.bf16.bf16 "
      "{%0,%1,%2,%3,%4,%5,%6,%7,%8,%9,%10,%11,%12,%13,%14,%15,%16,%17,%18,%19,%20,%21,%22,%23,%24,%25,%26,%27,%28,%29,%30,%31,%32,%33,%34,%35,%36,%37,%38,%39,%40,%41,%42,%43,%44,%45,%46,%47,%48,%49,%50,%51,%52,%53,%54,%55,%56,%57,%58,%59,%60,%61,%62,%63}, "
      "%64, %65, p, 1, 1, 0, 0;\n}\n"
      : "=f"(d[0]), "=f"(d[1]), "=f"(d[2]), "=f"(d[3]), "=f"(d[4]), "=f"(d[5]), "=f"(d[6]), "=f"(d[7]),
        "=f"(d[8]), "=f"(d[9]), "=f"(d[10]), "=f"(d[11]), "=f"(d[12]), "=f"(d[13]), "=f"(d[14]), "=f"(d[15]),
        "=f"(d[16]), "=f"(d[17]), "=f"(d[18]), "=f"(d[19]), "=f"(d[20]), "=f"(d[21]), "=f"(d[22]), "=f"(d[23]),
        "=f"(d[24]), "=f"(d[25]), "=f"(d[26]), "=f"(d[27]), "=f"(d[28]), "=f"(d[29]), "=f"(d[30]), "=f"(d[31]),
        "=f"(d[32]), "=f"(d[33]), "=f"(d[34]), "=f"(d[35]), "=f"(d[36]), "=f"(d[37]), "=f"(d[38]), "=f"(d[39]),
        "=f"(d[40]), "=f"(d[41]), "=f"(d[42]), "=f"(d[43]), "=f"(d[44]), "=f"(d[45]), "=f"(d[46]), "=f"(d[47]),
        "=f"(d[48]), "=f"(d[49]), "=f"(d[50]), "=f"(d[51]), "=f"(d[52]), "=f"(d[53]), "=f"(d[54]), "=f"(d[55]),
        "=f"(d[56]), "=f"(d[57]), "=f"(d[58]), "=f"(d[59]), "=f"(d[60]), "=f"(d[61]), "=f"(d[62]), "=f"(d[63])
      : "l"(da), "l"(db));
}
__device__ __forceinline__ void mma_ss128(float (&d)[64], uint64_t da, uint64_t db) {
  asm volatile("{\n.reg .pred p;\nsetp.ne.b32 p, 1, 0;\n"
      "wgmma.mma_async.sync.aligned.m64n128k16.f32.bf16.bf16 "
      "{%0,%1,%2,%3,%4,%5,%6,%7,%8,%9,%10,%11,%12,%13,%14,%15,%16,%17,%18,%19,%20,%21,%22,%23,%24,%25,%26,%27,%28,%29,%30,%31,%32,%33,%34,%35,%36,%37,%38,%39,%40,%41,%42,%43,%44,%45,%46,%47,%48,%49,%50,%51,%52,%53,%54,%55,%56,%57,%58,%59,%60,%61,%62,%63}, "
      "%64, %65, p, 1, 1, 0, 0;\n}\n"
      : "+f"(d[0]), "+f"(d[1]), "+f"(d[2]), "+f"(d[3]), "+f"(d[4]), "+f"(d[5]), "+f"(d[6]), "+f"(d[7]),
        "+f"(d[8]), "+f"(d[9]), "+f"(d[10]), "+f"(d[11]), "+f"(d[12]), "+f"(d[13]), "+f"(d[14]), "+f"(d[15]),
        "+f"(d[16]), "+f"(d[17]), "+f"(d[18]), "+f"(d[19]), "+f"(d[20]), "+f"(d[21]), "+f"(d[22]), "+f"(d[23]),
        "+f"(d[24]), "+f"(d[25]), "+f"(d[26]), "+f"(d[27]), "+f"(d[28]), "+f"(d[29]), "+f"(d[30]), "+f"(d[31]),
        "+f"(d[32]), "+f"(d[33]), "+f"(d[34]), "+f"(d[35]), "+f"(d[36]), "+f"(d[37]), "+f"(d[38]), "+f"(d[39]),
        "+f"(d[40]), "+f"(d[41]), "+f"(d[42]), "+f"(d[43]), "+f"(d[44]), "+f"(d[45]), "+f"(d[46]), "+f"(d[47]),
        "+f"(d[48]), "+f"(d[49]), "+f"(d[50]), "+f"(d[51]), "+f"(d[52]), "+f"(d[53]), "+f"(d[54]), "+f"(d[55]),
        "+f"(d[56]), "+f"(d[57]), "+f"(d[58]), "+f"(d[59]), "+f"(d[60]), "+f"(d[61]), "+f"(d[62]), "+f"(d[63])
      : "l"(da), "l"(db));
}
__device__ __forceinline__ void mma_ss64_z(float (&d)[32], uint64_t da, uint64_t db) {
  asm volatile("{\n.reg .pred p;\nsetp.ne.b32 p, 0, 0;\n"
      "wgmma.mma_async.sync.aligned.m64n64k16.f32.bf16.bf16 "
      "{%0,%1,%2,%3,%4,%5,%6,%7,%8,%9,%10,%11,%12,%13,%14,%15,%16,%17,%18,%19,%20,%21,%22,%23,%24,%25,%26,%27,%28,%29,%30,%31}, "
      "%32, %33, p, 1, 1, 0, 0;\n}\n"
      : "=f"(d[0]), "=f"(d[1]), "=f"(d[2]), "=f"(d[3]), "=f"(d[4]), "=f"(d[5]), "=f"(d[6]), "=f"(d[7]),
        "=f"(d[8]), "=f"(d[9]), "=f"(d[10]), "=f"(d[11]), "=f"(d[12]), "=f"(d[13]), "=f"(d[14]), "=f"(d[15]),
        "=f"(d[16]), "=f"(d[17]), "=f"(d[18]), "=f"(d[19]), "=f"(d[20]), "=f"(d[21]), "=f"(d[22]), "=f"(d[23]),
        "=f"(d[24]), "=f"(d[25]), "=f"(d[26]), "=f"(d[27]), "=f"(d[28]), "=f"(d[29]), "=f"(d[30]), "=f"(d[31])
      : "l"(da), "l"(db));
}
__device__ __forceinline__ void mma_ss64(float (&d)[32], uint64_t da, uint64_t db) {
  asm volatile("{\n.reg .pred p;\nsetp.ne.b32 p, 1, 0;\n"
      "wgmma.mma_async.sync.aligned.m64n64k16.f32.bf16.bf16 "
      "{%0,%1,%2,%3,%4,%5,%6,%7,%8,%9,%10,%11,%12,%13,%14,%15,%16,%17,%18,%19,%20,%21,%22,%23,%24,%25,%26,%27,%28,%29,%30,%31}, "
      "%32, %33, p, 1, 1, 0, 0;\n}\n"
      : "+f"(d[0]), "+f"(d[1]), "+f"(d[2]), "+f"(d[3]), "+f"(d[4]), "+f"(d[5]), "+f"(d[6]), "+f"(d[7]),
        "+f"(d[8]), "+f"(d[9]), "+f"(d[10]), "+f"(d[11]), "+f"(d[12]), "+f"(d[13]), "+f"(d[14]), "+f"(d[15]),
        "+f"(d[16]), "+f"(d[17]), "+f"(d[18]), "+f"(d[19]), "+f"(d[20]), "+f"(d[21]), "+f"(d[22]), "+f"(d[23]),
        "+f"(d[24]), "+f"(d[25]), "+f"(d[26]), "+f"(d[27]), "+f"(d[28]), "+f"(d[29]), "+f"(d[30]), "+f"(d[31])
      : "l"(da), "l"(db));
}
__device__ __forceinline__ void mma_pv32(float (&d)[16], uint32_t a0, uint32_t a1, uint32_t a2, uint32_t a3, uint64_t db) {
  asm volatile("{\n.reg .pred p;\nsetp.ne.b32 p, 1, 0;\n"
      "wgmma.mma_async.sync.aligned.m64n32k16.f32.bf16.bf16 "
      "{%0,%1,%2,%3,%4,%5,%6,%7,%8,%9,%10,%11,%12,%13,%14,%15}, "
      "{%16,%17,%18,%19}, %20, p, 1, 1, 1;\n}\n"
      : "+f"(d[0]), "+f"(d[1]), "+f"(d[2]), "+f"(d[3]), "+f"(d[4]), "+f"(d[5]), "+f"(d[6]), "+f"(d[7]),
        "+f"(d[8]), "+f"(d[9]), "+f"(d[10]), "+f"(d[11]), "+f"(d[12]), "+f"(d[13]), "+f"(d[14]), "+f"(d[15])
      : "r"(a0), "r"(a1), "r"(a2), "r"(a3), "l"(db));
}
__device__ __forceinline__ void mma_out32(float (&d)[16], uint64_t da, uint64_t db, int acc) {
  asm volatile("{\n.reg .pred p;\nsetp.ne.b32 p, %18, 0;\n"
      "wgmma.mma_async.sync.aligned.m64n32k16.f32.bf16.bf16 "
      "{%0,%1,%2,%3,%4,%5,%6,%7,%8,%9,%10,%11,%12,%13,%14,%15}, "
      "%16, %17, p, 1, 1, 1, 0;\n}\n"
      : "+f"(d[0]), "+f"(d[1]), "+f"(d[2]), "+f"(d[3]), "+f"(d[4]), "+f"(d[5]), "+f"(d[6]), "+f"(d[7]),
        "+f"(d[8]), "+f"(d[9]), "+f"(d[10]), "+f"(d[11]), "+f"(d[12]), "+f"(d[13]), "+f"(d[14]), "+f"(d[15])
      : "l"(da), "l"(db), "r"(acc));
}
__device__ __forceinline__ void mma_pp16(float (&d)[8], uint32_t a0, uint32_t a1, uint32_t a2, uint32_t a3, uint64_t db, int acc) {
  asm volatile("{\n.reg .pred p;\nsetp.ne.b32 p, %13, 0;\n"
      "wgmma.mma_async.sync.aligned.m64n16k16.f32.bf16.bf16 "
      "{%0,%1,%2,%3,%4,%5,%6,%7}, "
      "{%8,%9,%10,%11}, %12, p, 1, 1, 1;\n}\n"
      : "+f"(d[0]), "+f"(d[1]), "+f"(d[2]), "+f"(d[3]), "+f"(d[4]), "+f"(d[5]), "+f"(d[6]), "+f"(d[7])
      : "r"(a0), "r"(a1), "r"(a2), "r"(a3), "l"(db), "r"(acc));
}
__device__ __forceinline__ void mma_rs32(float (&d)[32], uint32_t a0, uint32_t a1, uint32_t a2, uint32_t a3, uint64_t db) {
  asm volatile("{\n.reg .pred p;\nsetp.ne.b32 p, 1, 0;\n"
      "wgmma.mma_async.sync.aligned.m64n32k16.f32.bf16.bf16 "
      "{%0,%1,%2,%3,%4,%5,%6,%7,%8,%9,%10,%11,%12,%13,%14,%15}, "
      "{%16,%17,%18,%19}, %20, p, 1, 1, 0;\n}\n"
      : "+f"(d[0]), "+f"(d[1]), "+f"(d[2]), "+f"(d[3]), "+f"(d[4]), "+f"(d[5]), "+f"(d[6]), "+f"(d[7]),
        "+f"(d[8]), "+f"(d[9]), "+f"(d[10]), "+f"(d[11]), "+f"(d[12]), "+f"(d[13]), "+f"(d[14]), "+f"(d[15])
      : "r"(a0), "r"(a1), "r"(a2), "r"(a3), "l"(db));
}
__device__ __forceinline__ void mma_rs40(float (&d)[32], uint32_t a0, uint32_t a1, uint32_t a2, uint32_t a3, uint64_t db) {
  asm volatile("{\n.reg .pred p;\nsetp.ne.b32 p, 1, 0;\n"
      "wgmma.mma_async.sync.aligned.m64n40k16.f32.bf16.bf16 "
      "{%0,%1,%2,%3,%4,%5,%6,%7,%8,%9,%10,%11,%12,%13,%14,%15,%16,%17,%18,%19}, "
      "{%20,%21,%22,%23}, %24, p, 1, 1, 0;\n}\n"
      : "+f"(d[0]), "+f"(d[1]), "+f"(d[2]), "+f"(d[3]), "+f"(d[4]), "+f"(d[5]), "+f"(d[6]), "+f"(d[7]),
        "+f"(d[8]), "+f"(d[9]), "+f"(d[10]), "+f"(d[11]), "+f"(d[12]), "+f"(d[13]), "+f"(d[14]), "+f"(d[15]),
        "+f"(d[16]), "+f"(d[17]), "+f"(d[18]), "+f"(d[19])
      : "r"(a0), "r"(a1), "r"(a2), "r"(a3), "l"(db));
}
__device__ __forceinline__ void mma_rs48(float (&d)[32], uint32_t a0, uint32_t a1, uint32_t a2, uint32_t a3, uint64_t db) {
  asm volatile("{\n.reg .pred p;\nsetp.ne.b32 p, 1, 0;\n"
      "wgmma.mma_async.sync.aligned.m64n48k16.f32.bf16.bf16 "
      "{%0,%1,%2,%3,%4,%5,%6,%7,%8,%9,%10,%11,%12,%13,%14,%15,%16,%17,%18,%19,%20,%21,%22,%23}, "
      "{%24,%25,%26,%27}, %28, p, 1, 1, 0;\n}\n"
      : "+f"(d[0]), "+f"(d[1]), "+f"(d[2]), "+f"(d[3]), "+f"(d[4]), "+f"(d[5]), "+f"(d[6]), "+f"(d[7]),
        "+f"(d[8]), "+f"(d[9]), "+f"(d[10]), "+f"(d[11]), "+f"(d[12]), "+f"(d[13]), "+f"(d[14]), "+f"(d[15]),
        "+f"(d[16]), "+f"(d[17]), "+f"(d[18]), "+f"(d[19]), "+f"(d[20]), "+f"(d[21]), "+f"(d[22]), "+f"(d[23])
      : "r"(a0), "r"(a1), "r"(a2), "r"(a3), "l"(db));
}
__device__ __forceinline__ void mma_rs56(float (&d)[32], uint32_t a0, uint32_t a1, uint32_t a2, uint32_t a3, uint64_t db) {
  asm volatile("{\n.reg .pred p;\nsetp.ne.b32 p, 1, 0;\n"
      "wgmma.mma_async.sync.aligned.m64n56k16.f32.bf16.bf16 "
      "{%0,%1,%2,%3,%4,%5,%6,%7,%8,%9,%10,%11,%12,%13,%14,%15,%16,%17,%18,%19,%20,%21,%22,%23,%24,%25,%26,%27}, "
      "{%28,%29,%30,%31}, %32, p, 1, 1, 0;\n}\n"
      : "+f"(d[0]), "+f"(d[1]), "+f"(d[2]), "+f"(d[3]), "+f"(d[4]), "+f"(d[5]), "+f"(d[6]), "+f"(d[7]),
        "+f"(d[8]), "+f"(d[9]), "+f"(d[10]), "+f"(d[11]), "+f"(d[12]), "+f"(d[13]), "+f"(d[14]), "+f"(d[15]),
        "+f"(d[16]), "+f"(d[17]), "+f"(d[18]), "+f"(d[19]), "+f"(d[20]), "+f"(d[21]), "+f"(d[22]), "+f"(d[23]),
        "+f"(d[24]), "+f"(d[25]), "+f"(d[26]), "+f"(d[27])
      : "r"(a0), "r"(a1), "r"(a2), "r"(a3), "l"(db));
}
__device__ __forceinline__ void mma_rs64(float (&d)[32], uint32_t a0, uint32_t a1, uint32_t a2, uint32_t a3, uint64_t db) {
  asm volatile("{\n.reg .pred p;\nsetp.ne.b32 p, 1, 0;\n"
      "wgmma.mma_async.sync.aligned.m64n64k16.f32.bf16.bf16 "
      "{%0,%1,%2,%3,%4,%5,%6,%7,%8,%9,%10,%11,%12,%13,%14,%15,%16,%17,%18,%19,%20,%21,%22,%23,%24,%25,%26,%27,%28,%29,%30,%31}, "
      "{%32,%33,%34,%35}, %36, p, 1, 1, 0;\n}\n"
      : "+f"(d[0]), "+f"(d[1]), "+f"(d[2]), "+f"(d[3]), "+f"(d[4]), "+f"(d[5]), "+f"(d[6]), "+f"(d[7]),
        "+f"(d[8]), "+f"(d[9]), "+f"(d[10]), "+f"(d[11]), "+f"(d[12]), "+f"(d[13]), "+f"(d[14]), "+f"(d[15]),
        "+f"(d[16]), "+f"(d[17]), "+f"(d[18]), "+f"(d[19]), "+f"(d[20]), "+f"(d[21]), "+f"(d[22]), "+f"(d[23]),
        "+f"(d[24]), "+f"(d[25]), "+f"(d[26]), "+f"(d[27]), "+f"(d[28]), "+f"(d[29]), "+f"(d[30]), "+f"(d[31])
      : "r"(a0), "r"(a1), "r"(a2), "r"(a3), "l"(db));
}

__device__ __forceinline__ void wg_fence() { asm volatile("wgmma.fence.sync.aligned;" ::: "memory"); }
__device__ __forceinline__ void wg_commit() { asm volatile("wgmma.commit_group.sync.aligned;" ::: "memory"); }
template <int N> __device__ __forceinline__ void wg_wait() { asm volatile("wgmma.wait_group.sync.aligned %0;" ::"n"(N) : "memory"); }
template <int N> __device__ __forceinline__ void pin(float (&d)[N]) {
#pragma unroll
  for (int i = 0; i < N; i++) asm volatile("" : "+f"(d[i])::"memory");
}
template <int N> __device__ __forceinline__ void pin(uint32_t (&d)[N]) {
#pragma unroll
  for (int i = 0; i < N; i++) asm volatile("" : "+r"(d[i])::"memory");
}
__device__ __forceinline__ uint64_t mkdesc(uint32_t addr, uint32_t lbo, uint32_t sbo, uint32_t swz) {
  return (uint64_t)(((addr & 0x3FFFF) >> 4) | ((lbo >> 4) << 16)) | ((uint64_t)((sbo >> 4) | (swz << 30)) << 32);
}
__device__ __forceinline__ void mbar_init(uint32_t b, int c) { asm volatile("mbarrier.init.shared::cta.b64 [%0], %1;" ::"r"(b), "r"(c) : "memory"); }
__device__ __forceinline__ void mbar_expect(uint32_t b, uint32_t n) {
  asm volatile("mbarrier.arrive.expect_tx.shared::cta.b64 _, [%0], %1;" ::"r"(b), "r"(n) : "memory");
}
__device__ __forceinline__ void mbar_arrive_remote(uint32_t b) { asm volatile("mbarrier.arrive.relaxed.cluster.shared::cluster.b64 _, [%0];" ::"r"(b) : "memory"); }
__device__ __forceinline__ void warp_arrive(uint32_t b, int lane) {
  __syncwarp();
  asm volatile("{\n.reg .pred p;\nsetp.eq.u32 p, %1, 0;\n@p mbarrier.arrive.shared::cta.b64 _, [%0];\n}" ::"r"(b), "r"(lane) : "memory");
}
__device__ __forceinline__ void mbar_arrive(uint32_t b) { asm volatile("mbarrier.arrive.shared::cta.b64 _, [%0];" ::"r"(b) : "memory"); }
__device__ __forceinline__ bool mbar_try(uint32_t b, uint32_t ph) {
  uint32_t ok;
  asm volatile("{\n.reg .pred p;\nmbarrier.try_wait.parity.shared::cta.b64 p, [%1], %2;\nselp.b32 %0, 1, 0, p;\n}" : "=r"(ok) : "r"(b), "r"(ph) : "memory");
  return ok;
}
__device__ __forceinline__ bool mbar_test(uint32_t b, uint32_t ph) {
  uint32_t ok;
  asm volatile("{\n.reg .pred p;\nmbarrier.test_wait.parity.shared::cta.b64 p, [%1], %2;\nselp.b32 %0, 1, 0, p;\n}" : "=r"(ok) : "r"(b), "r"(ph) : "memory");
  return ok;
}
__device__ __forceinline__ void mbar_wait(uint32_t b, uint32_t ph) {
  if (mbar_try(b, ph)) return;
  for (int i = 0; i < (1 << 20); i++)
    if (mbar_try(b, ph)) return;
}
__device__ __forceinline__ void mbar_wait_cluster(uint32_t b, uint32_t ph) {
  for (int i = 0; i < (1 << 20); i++) {
    uint32_t ok;
    asm volatile("{\n.reg .pred p;\nmbarrier.try_wait.parity.acquire.cluster.shared::cta.b64 p, [%1], %2;\nselp.b32 %0, 1, 0, p;\n}" : "=r"(ok) : "r"(b), "r"(ph) : "memory");
    if (ok) return;
  }
}
__device__ __forceinline__ void tma2d(uint32_t dst, const CUtensorMap* tm, int c0, int c1, uint32_t b) {
  asm volatile("cp.async.bulk.tensor.2d.shared::cluster.global.mbarrier::complete_tx::bytes [%0], [%1, {%3, %4}], [%2];" ::"r"(dst), "l"(tm), "r"(b), "r"(c0), "r"(c1) : "memory");
}
__device__ __forceinline__ void bulk_g2s(uint32_t dst, const void* src, uint32_t n, uint32_t b) {
  asm volatile("cp.async.bulk.shared::cluster.global.mbarrier::complete_tx::bytes [%0], [%1], %2, [%3];" ::"r"(dst), "l"(src), "r"(n), "r"(b) : "memory");
}
__device__ __forceinline__ bool elect_one() {
  uint32_t p;
  asm volatile("{\n.reg .pred p;\nelect.sync _|p, 0xffffffff;\nselp.b32 %0, 1, 0, p;\n}" : "=r"(p));
  return p;
}
__device__ __forceinline__ void wg_bar(int wg) { asm volatile("bar.sync %0, 128;" ::"r"(wg + 1) : "memory"); }
__device__ __forceinline__ void fence_async() { asm volatile("fence.proxy.async.shared::cta;" ::: "memory"); }
__device__ __forceinline__ void publish(unsigned* c) { asm volatile("red.release.gpu.global.add.u32 [%0], 1;" ::"l"(c) : "memory"); }
__device__ __forceinline__ unsigned ld_acquire(const unsigned* c) {
  unsigned v;
  asm volatile("ld.acquire.gpu.global.u32 %0, [%1];" : "=r"(v) : "l"(c) : "memory");
  return v;
}
__device__ __forceinline__ void poll(const unsigned* c, unsigned target) {
  for (int i = 0; i < (1 << 20); i++) {
    if ((int)(ld_acquire(c) - target) >= 0) return;
    __nanosleep(POLL_NS);
  }
}
__device__ __forceinline__ uint32_t mapa(uint32_t a, uint32_t rank) {
  uint32_t r;
  asm("mapa.shared::cluster.u32 %0, %1, %2;" : "=r"(r) : "r"(a), "r"(rank));
  return r;
}
__device__ __forceinline__ void sts32(uint32_t a, uint32_t v) { asm volatile("st.shared.b32 [%0], %1;" ::"r"(a), "r"(v) : "memory"); }
__device__ __forceinline__ void sts16(uint32_t a, uint16_t v) { asm volatile("st.shared.b16 [%0], %1;" ::"r"(a), "h"(v) : "memory"); }
__device__ __forceinline__ void stsf(uint32_t a, float v) { asm volatile("st.shared.f32 [%0], %1;" ::"r"(a), "f"(v) : "memory"); }
__device__ __forceinline__ void sts64(uint32_t a, uint32_t x, uint32_t y) { asm volatile("st.shared.v2.b32 [%0], {%1,%2};" ::"r"(a), "r"(x), "r"(y) : "memory"); }
__device__ __forceinline__ void sts128(uint32_t a, uint32_t x, uint32_t y, uint32_t z, uint32_t w) {
  asm volatile("st.shared.v4.b32 [%0], {%1,%2,%3,%4};" ::"r"(a), "r"(x), "r"(y), "r"(z), "r"(w) : "memory");
}
__device__ __forceinline__ uint32_t lds32(uint32_t a) { uint32_t v; asm volatile("ld.shared.b32 %0, [%1];" : "=r"(v) : "r"(a) : "memory"); return v; }
__device__ __forceinline__ float ldsf(uint32_t a) { float v; asm volatile("ld.shared.f32 %0, [%1];" : "=f"(v) : "r"(a) : "memory"); return v; }
__device__ __forceinline__ void lds64(uint32_t& x, uint32_t& y, uint32_t a) { asm volatile("ld.shared.v2.b32 {%0,%1}, [%2];" : "=r"(x), "=r"(y) : "r"(a) : "memory"); }
__device__ __forceinline__ uint4 lds128(uint32_t a) {
  uint4 v;
  asm volatile("ld.shared.v4.b32 {%0,%1,%2,%3}, [%4];" : "=r"(v.x), "=r"(v.y), "=r"(v.z), "=r"(v.w) : "r"(a) : "memory");
  return v;
}
__device__ __forceinline__ void ldsm4(uint32_t (&r)[4], uint32_t a) {
  asm volatile("ldmatrix.sync.aligned.m8n8.x4.shared.b16 {%0,%1,%2,%3}, [%4];" : "=r"(r[0]), "=r"(r[1]), "=r"(r[2]), "=r"(r[3]) : "r"(a) : "memory");
}
__device__ __forceinline__ void ldsm4t(uint32_t (&r)[4], uint32_t a) {
  asm volatile("ldmatrix.sync.aligned.m8n8.x4.trans.shared.b16 {%0,%1,%2,%3}, [%4];" : "=r"(r[0]), "=r"(r[1]), "=r"(r[2]), "=r"(r[3]) : "r"(a) : "memory");
}
__device__ __forceinline__ void stsm4t(uint32_t a, uint32_t r0, uint32_t r1, uint32_t r2, uint32_t r3) {
  asm volatile("stmatrix.sync.aligned.m8n8.x4.trans.shared.b16 [%0], {%1,%2,%3,%4};" ::"r"(a), "r"(r0), "r"(r1), "r"(r2), "r"(r3) : "memory");
}
__device__ __forceinline__ uint32_t ldcg32(const void* p) { uint32_t v; asm volatile("ld.global.cg.b32 %0, [%1];" : "=r"(v) : "l"(p) : "memory"); return v; }
__device__ __forceinline__ uint4 ldcg128(const void* p) {
  uint4 v;
  asm volatile("ld.global.cg.v4.b32 {%0,%1,%2,%3}, [%4];" : "=r"(v.x), "=r"(v.y), "=r"(v.z), "=r"(v.w) : "l"(p) : "memory");
  return v;
}
__device__ __forceinline__ float ex2f(float x) { float y; asm("ex2.approx.ftz.f32 %0, %1;" : "=f"(y) : "f"(x)); return y; }
__device__ __forceinline__ uint32_t pk_bf(float lo, float hi) { uint32_t r; asm("cvt.rn.bf16x2.f32 %0, %1, %2;" : "=r"(r) : "f"(hi), "f"(lo)); return r; }
__device__ __forceinline__ uint32_t pk_h(float lo, float hi) { uint32_t r; asm("cvt.rn.f16x2.f32 %0, %1, %2;" : "=r"(r) : "f"(hi), "f"(lo)); return r; }
__device__ __forceinline__ float bf_lo(uint32_t v) { return __uint_as_float(v << 16); }
__device__ __forceinline__ float bf_hi(uint32_t v) { return __uint_as_float(v & 0xFFFF0000u); }
__device__ __forceinline__ uint32_t prmt(uint32_t a, uint32_t b, uint32_t s) { uint32_t r; asm("prmt.b32 %0, %1, %2, %3;" : "=r"(r) : "r"(a), "r"(b), "r"(s)); return r; }
__device__ __forceinline__ uint32_t bf2_mul(uint32_t a, uint32_t b) { uint32_t r; asm("mul.rn.bf16x2 %0, %1, %2;" : "=r"(r) : "r"(a), "r"(b)); return r; }
__device__ __forceinline__ uint32_t bf2_fma(uint32_t a, uint32_t b, uint32_t c) { uint32_t r; asm("fma.rn.bf16x2 %0, %1, %2, %3;" : "=r"(r) : "r"(a), "r"(b), "r"(c)); return r; }
__device__ __forceinline__ uint32_t bf2_add(uint32_t a, uint32_t b) { uint32_t r; asm("add.rn.bf16x2 %0, %1, %2;" : "=r"(r) : "r"(a), "r"(b)); return r; }
__device__ __forceinline__ uint32_t bf2_sub(uint32_t a, uint32_t b) { uint32_t r; asm("sub.rn.bf16x2 %0, %1, %2;" : "=r"(r) : "r"(a), "r"(b)); return r; }

struct C2 { float r, i; };
__device__ __forceinline__ C2 cmul(C2 a, C2 b) { return {fmaf(a.r, b.r, -a.i * b.i), fmaf(a.r, b.i, a.i * b.r)}; }
__device__ __forceinline__ C2 anchor(float ar, float tr, float L) {
  float m = ex2f(ar * L), f = tr * L;
  f = (f - rintf(f)) * 6.283185307179586f;
  return {m * __cosf(f), m * __sinf(f)};
}
__device__ __forceinline__ C2 cmulc(C2 a, C2 b) { return {fmaf(a.r, b.r, a.i * b.i), fmaf(a.i, b.r, -a.r * b.i)}; }
__device__ __forceinline__ uint32_t h2_mul(uint32_t a, uint32_t b) { uint32_t r; asm("mul.rn.f16x2 %0, %1, %2;" : "=r"(r) : "r"(a), "r"(b)); return r; }
__device__ __forceinline__ uint32_t h2_fma(uint32_t a, uint32_t b, uint32_t c) { uint32_t r; asm("fma.rn.f16x2 %0, %1, %2, %3;" : "=r"(r) : "r"(a), "r"(b), "r"(c)); return r; }
__device__ __forceinline__ uint32_t h2_neg(uint32_t a) { uint32_t r; asm("neg.f16x2 %0, %1;" : "=r"(r) : "r"(a)); return r; }
__device__ __forceinline__ void mma_h(float (&c)[4], const uint32_t (&a)[4], uint32_t b0, uint32_t b1) {
  asm volatile("mma.sync.aligned.m16n8k16.row.col.f32.f16.f16.f32 {%0,%1,%2,%3}, {%4,%5,%6,%7}, {%8,%9}, {%0,%1,%2,%3};"
               : "+f"(c[0]), "+f"(c[1]), "+f"(c[2]), "+f"(c[3]) : "r"(a[0]), "r"(a[1]), "r"(a[2]), "r"(a[3]), "r"(b0), "r"(b1));
}

struct KgBase { C2 z1, z8, z256, z2, y[3]; };
__device__ __forceinline__ KgBase kgen_base(uint32_t are, uint32_t aim, float dt) {
  const float ar = bf_lo(are) * dt * 1.4426950408889634f, tr = bf_lo(aim) * dt * 0.15915494309189535f;
  KgBase k;
  k.z1 = anchor(ar, tr, 1.f); k.z8 = anchor(ar, tr, 8.f); k.z256 = anchor(ar, tr, 256.f); k.y[0] = anchor(ar, tr, 64.f);
  k.y[1] = cmul(k.y[0], k.y[0]); k.y[2] = cmul(k.y[1], k.y[0]);
  k.z2 = cmul(k.z1, k.z1);
  return k;
}
__device__ __forceinline__ void kgen_rows(uint32_t wbase, int lane, const KgBase& k, C2 cb) {
  const uint32_t rx = wbase + lane * 32, rw = wbase + 4096 + lane * 96, s1 = (lane & 4) << 2;
  C2 x[8], w[8], p[8];
  x[0] = {1.f, 0.f}; x[1] = k.z8; w[0] = cb; p[0] = cmulc(cb, k.z256);
#pragma unroll
  for (int a = 1; a < 8; a++) { if (a > 1) x[a] = cmul(x[a - 1], k.z8); w[a] = cmulc(w[a - 1], k.z1); p[a] = cmulc(p[a - 1], k.z256); }
  const uint32_t ry = wbase + 1024 + ((lane >> 1) & 3) * 160 + (lane >> 3) * 24 + (lane & 1) * 2;
#pragma unroll
  for (int b = 0; b < 3; b++) { const uint32_t v = pk_h(k.y[b].r, k.y[b].i); sts16(ry + 8 * b, (uint16_t)v); sts16(ry + 8 * b + 4, (uint16_t)(v >> 16)); }
  sts128(rx + s1, pk_h(x[0].r, x[1].r), pk_h(x[2].r, x[3].r), pk_h(x[4].r, x[5].r), pk_h(x[6].r, x[7].r));
  sts128(rx + (16 ^ s1), pk_h(x[0].i, x[1].i), pk_h(x[2].i, x[3].i), pk_h(x[4].i, x[5].i), pk_h(x[6].i, x[7].i));
  sts128(rw + s1, pk_h(w[0].r, w[1].r), pk_h(w[2].r, w[3].r), pk_h(w[4].r, w[5].r), pk_h(w[6].r, w[7].r));
  sts128(rw + (16 ^ s1), pk_h(w[0].i, w[1].i), pk_h(w[2].i, w[3].i), pk_h(w[4].i, w[5].i), pk_h(w[6].i, w[7].i));
  sts128(rw + 32 + s1, pk_h(p[0].r, p[1].r), pk_h(p[2].r, p[3].r), pk_h(p[4].r, p[5].r), pk_h(p[6].r, p[7].r));
  sts128(rw + 32 + (16 ^ s1), pk_h(p[0].i, p[1].i), pk_h(p[2].i, p[3].i), pk_h(p[4].i, p[5].i), pk_h(p[6].i, p[7].i));
  const C2 e0 = cmulc(p[0], k.z2), e1 = cmulc(e0, k.z2), e2 = cmulc(e1, k.z2), e3 = cmulc(e1, k.z256), e4 = cmulc(e3, k.z256);
  sts128(rw + 64 + s1, pk_h(e0.r, e1.r), pk_h(e2.r, e3.r), pk_h(e4.r, 0.f), 0u);
  sts128(rw + 64 + (16 ^ s1), pk_h(e0.i, e1.i), pk_h(e2.i, e3.i), pk_h(e4.i, 0.f), 0u);
  __syncwarp();
}
__device__ __forceinline__ void kgen_mma(uint32_t wbase, int lane, float (&acc)[2][3][4]) {
  const int m = lane >> 3, r = lane & 7;
#pragma unroll
  for (int ks = 0; ks < 2; ks++) {
    uint32_t b[3][4], x[4], y[12];
    const uint32_t sw = (((m >> 1) ^ (r >> 2)) & 1) << 4;
    const uint32_t ab = wbase + 4096 + (16 * ks + 8 * (m & 1) + r) * 96 + sw;
    ldsm4t(x, wbase + (16 * ks + 8 * (m & 1) + r) * 32 + sw);
#pragma unroll
    for (int q = 0; q < 3; q++) { const uint4 v = lds128(wbase + 1024 + (lane & 3) * 160 + ks * 48 + q * 16); y[4 * q] = v.x; y[4 * q + 1] = v.y; y[4 * q + 2] = v.z; y[4 * q + 3] = v.w; }
#pragma unroll
    for (int nt = 0; nt < 3; nt++) ldsm4t(b[nt], ab + nt * 32);
    uint32_t er[4][2], ei[4][2];
#pragma unroll
    for (int kh = 0; kh < 2; kh++) {
      er[0][kh] = x[kh]; ei[0][kh] = x[2 + kh];
#pragma unroll
      for (int q = 0; q < 3; q++) {
        const uint32_t yr = y[6 * kh + 2 * q], yi = y[6 * kh + 2 * q + 1];
        er[q + 1][kh] = h2_fma(h2_neg(x[2 + kh]), yi, h2_mul(x[kh], yr));
        ei[q + 1][kh] = h2_fma(x[2 + kh], yr, h2_mul(x[kh], yi));
      }
    }
#pragma unroll
    for (int mt = 0; mt < 2; mt++) {
      const uint32_t ar[4] = {er[2 * mt][0], er[2 * mt + 1][0], er[2 * mt][1], er[2 * mt + 1][1]};
      const uint32_t ai[4] = {ei[2 * mt][0], ei[2 * mt + 1][0], ei[2 * mt][1], ei[2 * mt + 1][1]};
#pragma unroll
      for (int nt = 0; nt < 3; nt++) mma_h(acc[mt][nt], ar, b[nt][0], b[nt][1]);
#pragma unroll
      for (int nt = 0; nt < 3; nt++) mma_h(acc[mt][nt], ai, b[nt][2], b[nt][3]);
    }
  }
}
__device__ __forceinline__ void kgen_store(uint32_t wbase, int warp, int lane, const float (&acc)[2][3][4], float isc) {
  __syncwarp();
  const uint32_t pa = wbase + (warp & 1) * 3712 + ((lane & 3) * 2 * 36 + (lane >> 2)) * 4;
#pragma unroll
  for (int mt = 0; mt < 2; mt++)
#pragma unroll
    for (int nt = 0; nt < 3; nt++)
#pragma unroll
      for (int c = 0; c < 4; c++) stsf(pa + ((8 * nt + (c & 1)) * 36 + 16 * mt + 8 * (c >> 1)) * 4, acc[mt][nt][c] * isc);
}

__device__ __forceinline__ int kidx(int tid, int q) { return q < 2 ? 2 * tid + q : 128 * (1 + (q >> 1)) + tid + (q & 1); }
__device__ __forceinline__ int kword(int idx) {
  const int u = idx & 127;
  if (idx < 256) return (idx & 7) * 36 + (idx >> 3);
  if (idx < 384) return ((u & 3) ? 15 + (u & 3) : 8) * 36 + (u >> 2);
  if (idx < 512) return (9 + (u >> 6) + 10 * (u & 1)) * 36 + ((u & 63) >> 1);
  return (11 + ((idx - 512) >> 5)) * 36 + (u & 31);
}
__device__ __forceinline__ float ksum(uint32_t stg, int idx) {
  const uint32_t a = stg + kword(idx) * 4;
  return (ldsf(a) + ldsf(a + 10880)) + (ldsf(a + 14336) + ldsf(a + 25216));
}

template <int G> struct ConvStep;
#define CONV_STEP(G, FN) \
  template <> struct ConvStep<G> { \
    static __device__ __forceinline__ void go(float (&d)[32], uint32_t a0, uint32_t a1, uint32_t a2, uint32_t a3, uint64_t db) { FN(d, a0, a1, a2, a3, db); } \
  };
CONV_STEP(0, mma_rs64) CONV_STEP(1, mma_rs56) CONV_STEP(2, mma_rs48) CONV_STEP(3, mma_rs40)
#undef CONV_STEP

__device__ __forceinline__ void toep_load(uint32_t* a, uint32_t q) {
  const uint32_t w0 = lds32(q), w1 = lds32(q - 4), w2 = lds32(q - 8), w3 = lds32(q - 12), w4 = lds32(q - 16);
  a[0] = prmt(w0, w1, 0x5432); a[1] = w0; a[2] = prmt(w1, w2, 0x5432); a[3] = w1;
  a[4] = prmt(w2, w3, 0x5432); a[5] = w2; a[6] = prmt(w3, w4, 0x5432); a[7] = w3;
}
__device__ __forceinline__ void conv_load(uint32_t (&a)[16], uint32_t pt, int pair) {
  toep_load(a, pt + 64 * pair * 4);
  toep_load(a + 8, pt + (64 * pair + 32) * 4);
}
template <int G, int H>
__device__ __forceinline__ void conv_issue(float (&acc)[32], uint32_t (&a)[16], uint64_t du) {
  pin(a);
  wg_fence();
#pragma unroll
  for (int s = 0; s < 2; s++) {
    const uint32_t* q = a + 8 * s;
    const uint64_t d = du + 8 * G + 4 * H + 2 * s;
    if (G == 0 && H == 0 && s == 0) mma_rs64_z(acc, q[0], q[1], q[2], q[3], (d));
    else ConvStep<G>::go(acc, q[0], q[1], q[2], q[3], (d));
    ConvStep<G>::go(acc, q[4], q[5], q[6], q[7], (d + 2 * (U_LBO >> 4)));
  }
  wg_commit();
}
template <int G>
__device__ __forceinline__ void conv_group(float (&acc)[32], uint32_t (&a0)[16], uint32_t (&a1)[16], uint32_t pt, uint64_t du) {
  conv_issue<G, 0>(acc, a0, du);
  conv_load(a1, pt, 2 * G + 1);
  conv_issue<G, 1>(acc, a1, du);
  wg_wait<1>();
  if (G < 3) conv_load(a0, pt, 2 * G + 2);
  else toep_load(a0, pt + 512 * 4);
  wg_wait<0>();
#pragma unroll
  for (int i = 0; i < 32 - 4 * G; i++) { float v; asm volatile("mov.b32 %0, %1;" : "=f"(v) : "f"(acc[i]) : "memory"); acc[i] = v; }
}

struct ChanIn { float gv[8], gw[8], dskip; };

__device__ __forceinline__ void load_u(const Params& p, int ch, uint32_t ut, uint32_t bar) {
  mbar_expect(bar, 4096);
#pragma unroll
  for (int kc = 0; kc < 4; kc++) bulk_g2s(ut + kc * U_LBO, p.g->xT + ch * SEQ + kc * 512, 1024, bar);
}
__device__ __forceinline__ void fetch_next(const Params& p, ChanIn& in, int next, int tid) {
  const float* kp = p.g->Kp + (next - CH_HAND) * 2 * KP_STRIDE;
#pragma unroll
  for (int q = 0; q < 8; q++) {
    in.gv[q] = __uint_as_float(ldcg32(kp + kidx(tid, q)));
    in.gw[q] = __uint_as_float(ldcg32(kp + KP_STRIDE + kidx(tid, q)));
  }
  in.dskip = bf_lo(__ldg(p.dsk + next));
}

__device__ __forceinline__ void far_sums(uint32_t b3, uint32_t ut, int tid) {
  const int oc = tid ? tid - 2 : 126;
  uint32_t w[8];
#pragma unroll
  for (int k = 0; k < 8; k++) {
    const int o = oc + (k < 2 ? -1 : k < 6 ? 0 : 1);
    w[k] = lds32(ut + ((k + 2) & 3) * U_LBO + (63 - (o >> 2)) * 16 + (o & 3) * 4);
  }
  float L[9], R[9];
  L[0] = 0.f; R[0] = 0.f;
#pragma unroll
  for (int k = 0; k < 4; k++) {
    L[2 * k + 1] = L[2 * k] + bf_hi(w[3 - k]); L[2 * k + 2] = L[2 * k + 1] + bf_lo(w[3 - k]);
    R[2 * k + 1] = R[2 * k] + bf_lo(w[4 + k]); R[2 * k + 2] = R[2 * k + 1] + bf_hi(w[4 + k]);
  }
  uint32_t u9[4], u7[4];
#pragma unroll
  for (int k = 0; k < 4; k++) {
    u9[k] = tid ? pk_bf(L[8 - 2 * k] + R[2 * k + 1], L[7 - 2 * k] + R[2 * k + 2]) : 0u;
    u7[k] = pk_bf(L[7 - 2 * k] + R[2 * k], L[6 - 2 * k] + R[2 * k + 1]);
  }
  const int i9 = tid >> 1, s7 = oc + 1, i7 = s7 >> 1;
  const int r9 = (4 * (i9 >> 5) + (i9 >> 1 & 3)) * 320 + (2 * (i9 >> 3 & 3) + (i9 & 1)) * 16 + (tid & 1) * 160;
  const int r7 = (4 * (i7 >> 5) + (i7 >> 1 & 3)) * 320 + (2 * (i7 >> 3 & 3) + (i7 & 1)) * 16 + (s7 & 1) * 160;
  sts128(b3 + r9, u9[0], u9[1], u9[2], u9[3]);
  sts128(b3 + 2560 + r7, u7[0], u7[1], u7[2], u7[3]);
}
__device__ __forceinline__ void conv_channel(const Params& p, uint32_t stg, uint32_t ut, uint32_t ut_next, uint32_t ubar, int upar, int wg, int tid, int ch,
                                             ChanIn& in, int next, uint32_t kpbar, uint32_t mb) {
  asm volatile("" : "+r"(stg), "+r"(tid));
  const int warp = __shfl_sync(0xffffffffu, tid >> 5, 0), lane = tid & 31, g = lane >> 2, t = lane & 3;
  const uint32_t pt0 = stg + ST_PT, t3 = stg + ST_T3;
  {
    const bool odd = tid & 1;
    if (tid == 0) in.gw[0] += in.dskip;
    float v[8];
#pragma unroll
    for (int q = 0; q < 8; q++) v[q] = in.gv[q] + in.gw[q];
    const uint32_t w1 = pk_bf(v[3], v[2]), w2 = pk_bf(v[5], v[4]), w3 = pk_bf(v[7], v[6]);
    sts32(pt0 + (16 + tid) * 4, pk_bf(v[1], v[0]));
    sts32(pt0 + (144 + tid) * 4, odd ? w1 : prmt(w1, w1, 0x3232));
    sts64(pt0 + (272 + 2 * tid) * 4, prmt(w2, w2, 0x3232), prmt(w2, w2, odd ? 0x1010 : 0x3210));
    sts16(t3 + (odd ? 128 : 384) + (tid >> 2) * 4 + ((tid & 2) ? 0 : 2), (uint16_t)w3);
    if (tid < 32) {
      const uint32_t c = __shfl_sync(0xffffffffu, w3, 0) & 0xFFFF0000u;
      sts32(pt0 + (528 + tid) * 4, tid < 2 ? c | (c >> 16) : tid == 2 ? c : 0u);
      sts32(t3 + tid * 4, 0u); sts32(t3 + 256 + tid * 4, 0u);
      sts16(pt0 + tid * 2, 0);
    }
  }
  TS(3);
  if (mb) warp_arrive(mb + B_T3 + 8 * wg, lane);
  mbar_wait(ubar, upar);
  if (!mb) {
    far_sums(stg + ST_B3, ut, tid);
    fence_async();
  }
  wg_bar(wg);
  TS(4);
  float acc[32];
  {
    const uint32_t pt = pt0 + 64 + (8 * warp + g - 4 * t) * 4;
    const uint64_t du = mkdesc(ut, U_LBO, 128, 0);
    uint32_t a0[16], a1[16];
    conv_load(a0, pt, 0);
    conv_group<0>(acc, a0, a1, pt, du);
    conv_group<1>(acc, a0, a1, pt, du);
    if (next >= 0) {
      if (next >= CH_HAND + 16) fetch_next(p, in, next, tid);
      if (tid == 0) load_u(p, next, ut_next, ubar);
      __syncwarp();
    }
    conv_group<2>(acc, a0, a1, pt, du);
    conv_group<3>(acc, a0, a1, pt, du);
    float d3[8];
    uint32_t a2[8];
    const uint32_t tf = t3 + (8 * warp + g - 4 * t) * 4;
    const uint64_t db = mkdesc(stg + ST_B3, 320, 160, 0);
    toep_load(a0 + 8, tf + 128); toep_load(a1, tf + 64); toep_load(a1 + 8, tf + 384); toep_load(a2, tf + 320);
    if (mb) mbar_wait(mb + B_X2 + 8 * wg, 0);
    pin(a0); pin(a1); pin(a2);
    wg_fence();
    mma_rs32(acc, a0[0], a0[1], a0[2], a0[3], du + 32);
    mma_rs32(acc, a0[4], a0[5], a0[6], a0[7], du + 32 + 2 * (U_LBO >> 4));
    mma_pp16(d3, a0[8], a0[9], a0[10], a0[11], db, 0);
    mma_pp16(d3, a0[12], a0[13], a0[14], a0[15], db + 40, 1);
#pragma unroll
    for (int k = 0; k < 4; k++) mma_pp16(d3, a1[4 * k], a1[4 * k + 1], a1[4 * k + 2], a1[4 * k + 3], db + (k < 2 ? 80 : 80) + 40 * k, 1);
    mma_pp16(d3, a2[0], a2[1], a2[2], a2[3], db + 240, 1);
    mma_pp16(d3, a2[4], a2[5], a2[6], a2[7], db + 280, 1);
    wg_commit();
    wg_wait<0>();
    pin(acc); pin(d3);
    const uint32_t x2 = stg + ST_X2 + ((8 * warp + g) * 36 + 2 * t) * 4;
#pragma unroll
    for (int k = 0; k < 4; k++) sts64(x2 + (16 * (k & 1) + 8 * (k >> 1)) * 4, __float_as_uint(d3[2 * k]), __float_as_uint(d3[2 * k + 1]));
    if (next >= 0 && next < CH_HAND + 16) {
      mbar_wait(kpbar, 0);
      fetch_next(p, in, next, tid);
    }
  }
  TS(5);
  const int b0 = 16 * (warp & 1) + 2 * g;
  uint32_t* dst = reinterpret_cast<uint32_t*>(p.g->bT + ch * SEQ + b0);
  const uint32_t xb = stg + ST_X + b0 * 4;
  if (warp >= 2) {
    const uint32_t xa = xb + 36 * (64 - 2 * t) * 4;
#pragma unroll
    for (int i = 0; i < 8; i++) {
      const int k = 4 * (i >> 1) + (i & 1), c = 8 * (i >> 1) + (i & 1);
      if (i == 0 && t == 0) { acc[0] = acc[16]; acc[2] = acc[18]; sts64(xb, 0u, 0u); }
      else sts64(xa - (32 + c) * 144, __float_as_uint(acc[16 + k]), __float_as_uint(acc[18 + k]));
    }
    wg_bar(wg);
#pragma unroll
    for (int i = 0; i < 8; i++) {
      const int k = 4 * (i >> 1) + (i & 1), c = 8 * (i >> 1) + (i & 1), d = (i == 0 && t == 0) ? 32 : c;
      uint32_t x, y, z, w;
      lds64(x, y, xa - d * 144);
      lds64(z, w, xa + (ST_X2 - ST_X) - (32 + d) * 144);
      dst[16 * (64 - 2 * t - d)] = pk_bf(acc[k] + __uint_as_float(x) + __uint_as_float(z), acc[2 + k] + __uint_as_float(y) + __uint_as_float(w));
    }
  } else {
    const uint32_t xa = xb + 36 * (63 - 2 * t) * 4;
#pragma unroll
    for (int i = 0; i < 8; i++) {
      const int k = 4 * (i >> 1) + (i & 1), c = 8 * (i >> 1) + (i & 1);
      sts64(xa - c * 144, __float_as_uint(acc[k]), __float_as_uint(acc[2 + k]));
    }
    wg_bar(wg);
#pragma unroll
    for (int i = 0; i < 8; i++) {
      const int k = 4 * (i >> 1) + (i & 1), c = 8 * (i >> 1) + (i & 1);
      uint32_t x, y;
      lds64(x, y, xa - (32 + c) * 144);
      dst[16 * (31 - 2 * t - c)] = pk_bf(acc[16 + k] + __uint_as_float(x), acc[18 + k] + __uint_as_float(y));
    }
  }
}

__device__ __forceinline__ uint32_t ex2_packed(float a0, float a1) {
  uint32_t r;
  asm("{\n.reg .b32 v, y, s, h;\n"
      "prmt.b32 v, %1, %2, 0x6521;\n"
      "lop3.b32 y, v, 0x007F007F, 0x3F803F80, 0xEA;\n"
      "fma.rn.bf16x2 s, y, %3, %4;\n"
      "fma.rn.bf16x2 h, s, y, %5;\n"
      "sub.u32 v, v, h;\n"
      "add.u32 %0, v, 0xC2FFC300;\n}\n"
      : "=r"(r) : "r"(__float_as_uint(a0)), "r"(__float_as_uint(a1)), "r"(0xC22AC22Au), "r"(0x43014301u), "r"(0x42264226u));
  return r;
}
__device__ __forceinline__ void qk_half(float (&s)[32], const uint32_t (&q)[8], uint64_t dk) {
  mma_rs64_z(s, q[0], q[1], q[2], q[3], (dk));
  mma_rs64(s, q[4], q[5], q[6], q[7], (dk + 2));
}
__device__ __forceinline__ void pv_half(float (&o)[16], const uint32_t (&p)[16], uint64_t dv) {
#pragma unroll
  for (int k = 0; k < 4; k++) mma_pv32(o, p[4 * k], p[4 * k + 1], p[4 * k + 2], p[4 * k + 3], (dv + k * 64));
}

__device__ __forceinline__ void attn_fast(float (&o)[16], uint32_t sb, int wg, int lane) {
  const uint32_t mb = sb + SM_MISC;
  uint64_t d0 = mkdesc(sb + SM_RING, 16, 512, 2), dq = mkdesc(sb + SM_QS + wg * 4096, 16, 512, 2);
  mbar_wait(mb + B_FULLKV, 0);
#pragma unroll 1
  for (int it = 0; it < 4; it++) {
#pragma unroll
    for (int st = 0; st < 4; st++) {
      asm volatile("" : "+l"(d0), "+l"(dq));
      const uint64_t dk = d0 + st * 1024, dv = dk + 512;
      uint32_t pa[16], pb[16];
      float sa[32], sc[32];
      wg_fence();
      mma_ss64_z(sa, dq, dk); mma_ss64(sa, dq + 2, dk + 2); wg_commit();
      mma_ss64_z(sc, dq, dk + 256); mma_ss64(sc, dq + 2, dk + 258); wg_commit();
      wg_wait<1>();
      pin(sa);
#pragma unroll
      for (int k = 0; k < 16; k++) pa[k] = ((EMU_MASK >> (k >> 1)) & 1) ? ex2_packed(sa[2 * k], sa[2 * k + 1]) : pk_bf(ex2f(sa[2 * k]), ex2f(sa[2 * k + 1]));
      pin(pa);
      wg_wait<0>();
      pin(sc);
      wg_fence();
      pv_half(o, pa, dv); wg_commit();
#pragma unroll
      for (int k = 0; k < 16; k++) pb[k] = ((EMU_MASK >> (8 + (k >> 1))) & 1) ? ex2_packed(sc[2 * k], sc[2 * k + 1]) : pk_bf(ex2f(sc[2 * k]), ex2f(sc[2 * k + 1]));
      pin(pb);
      wg_fence();
      pv_half(o, pb, dv + 256); wg_commit();
      const uint32_t nb = mb + B_FULLKV + 8 * ((st + 1) & 3), np = (st == 3 ? it + 1 : it) & 1;
      const bool ready = mbar_test(nb, np);
      wg_wait<0>();
      pin(o);
      warp_arrive(mb + B_EMPTY + 8 * st, lane);
      if (!ready) { if (st < 3 || it < 3) mbar_wait(nb, np); }
    }
  }
}

__device__ __forceinline__ void attn_safe(float (&o)[16], const uint32_t (&q)[8], uint32_t sb, int lane) {
  const uint32_t mb = sb + SM_MISC;
  const uint64_t d0 = mkdesc(sb + SM_RING, 16, 512, 2);
  float m0 = -INFINITY, m1 = -INFINITY;
#pragma unroll 1
  for (int tile = 0; tile < 16; tile++) {
    const uint64_t dk = d0 + (tile & 3) * 1024;
    mbar_wait(mb + B_FULLKV + 8 * (tile & 3), (tile >> 2) & 1);
#pragma unroll 1
    for (int hf = 0; hf < 2; hf++) {
      float s[32];
      uint32_t p[16];
      wg_fence();
      qk_half(s, q, dk + hf * 256); wg_commit();
      wg_wait<0>();
      pin(s);
      float n0 = m0, n1 = m1;
#pragma unroll
      for (int j = 0; j < 8; j++) {
        n0 = fmaxf(n0, fmaxf(s[4 * j], s[4 * j + 1]));
        n1 = fmaxf(n1, fmaxf(s[4 * j + 2], s[4 * j + 3]));
      }
      n0 = fmaxf(n0, __shfl_xor_sync(0xffffffffu, n0, 1)); n0 = fmaxf(n0, __shfl_xor_sync(0xffffffffu, n0, 2));
      n1 = fmaxf(n1, __shfl_xor_sync(0xffffffffu, n1, 1)); n1 = fmaxf(n1, __shfl_xor_sync(0xffffffffu, n1, 2));
      const float c0 = ex2f(m0 - n0), c1 = ex2f(m1 - n1);
      m0 = n0; m1 = n1;
#pragma unroll
      for (int j = 0; j < 4; j++) { o[4 * j] *= c0; o[4 * j + 1] *= c0; o[4 * j + 2] *= c1; o[4 * j + 3] *= c1; }
#pragma unroll
      for (int j = 0; j < 8; j++) {
        p[2 * j] = pk_bf(ex2f(s[4 * j] - n0), ex2f(s[4 * j + 1] - n0));
        p[2 * j + 1] = pk_bf(ex2f(s[4 * j + 2] - n1), ex2f(s[4 * j + 3] - n1));
      }
      pin(p); pin(o);
      wg_fence();
      pv_half(o, p, dk + 512 + hf * 256); wg_commit();
      wg_wait<0>();
      pin(o);
    }
    warp_arrive(mb + B_EMPTY + 8 * (tile & 3), lane);
  }
}

__device__ __forceinline__ int qkv_chunk(int cg, int i) { const int c = ((112 * cg) >> 6) + i; return c >= 7 ? c - 7 : c; }
__device__ __forceinline__ void qkv_issue(uint32_t sb, const CUtensorMap* tx, const CUtensorMap* twq, const CUtensorMap* twq48, int i, int b) {
  const int cg = b & 3, c = qkv_chunk(cg, i), st = i >= 6 ? 0 : i >= 3 ? i - 3 : i;
  const uint32_t bar = sb + SM_MISC + B_FULLA + 8 * st, dst = sb + SM_RING + st * 24576;
  mbar_expect(bar, i < 3 ? 14336 : 22528);
  if (i >= 3) tma2d(dst, tx, c * 64, (b >> 2) * 64, bar);
  tma2d(dst + 8192, twq, cg * 112, c * 64, bar);
  tma2d(dst + 16384, twq48, cg * 112 + 64, c * 64, bar);
}

__device__ __forceinline__ void proj_transpose(const Params& p, uint32_t sb, int tid, int warp) {
  const int b = blockIdx.x, tb = b >> 2, cg = b & 3, lane = tid & 31, c0 = (112 * cg) >> 6;
  TS(13);
  mbar_wait(sb + SM_MISC + B_XA, 0);
  TS(14);
  const int tok = 32 * (1 - (lane >> 1 & 1)) + 8 * (lane >> 3) + 4 * (warp & 1) + 2 * (lane >> 2 & 1) + (lane & 1), o0 = 14 * cg + (warp >> 1);
  uint32_t v[7][4];
#pragma unroll
  for (int i = 0; i < 7; i++) {
    const int oct = o0 + 2 * i;
    ldsm4t(v[i], sb + SM_RING + ((oct >> 3) - c0) * 24576 + tok * 128 + (((oct ^ tok) & 7) << 4));
  }
  uint16_t* dst = p.g->xT + (8 * o0 + (lane >> 2)) * SEQ + (2 * (warp & 1) + (lane >> 1 & 1)) * 512 + (62 - 2 * tb + (lane & 1)) * 8;
#pragma unroll
  for (int i = 0; i < 7; i++) *reinterpret_cast<uint4*>(dst + 16 * i * SEQ) = make_uint4(v[i][0], v[i][1], v[i][2], v[i][3]);
  warp_arrive(sb + SM_MISC + B_SXT, lane);
}

template <int H>
__device__ __forceinline__ void proj_half(float (&aq)[56], float (&ak)[8], uint32_t (&a)[2][4], uint32_t sb, uint32_t arow, uint32_t asw, int lane) {
  constexpr int I = H >> 1, st = I % 3, k0 = 2 * (H & 1);
  if (!(H & 1)) mbar_wait(sb + SM_MISC + B_FULLA + 8 * st, (I / 3) & 1);
  const uint32_t base = sb + SM_RING + st * 24576;
  ldsm4(a[0], base + arow + ((32 * k0) ^ asw));
  ldsm4(a[1], base + arow + ((32 * k0 + 32) ^ asw));
  const uint64_t db = mkdesc(base + 8192, 8192, 1024, 1) + 128 * k0, d2 = mkdesc(sb + SM_B2 + I * 2048, 256, 128, 0) + 32 * k0;
  pin(a[0]); pin(a[1]);
  wg_fence();
#pragma unroll
  for (int k = 0; k < 2; k++) {
    mma_q112(aq, a[k][0], a[k][1], a[k][2], a[k][3], db + 128 * k, H | k);
    mma_pp16(ak, a[k][0], a[k][1], a[k][2], a[k][3], d2 + 32 * k, H | k);
  }
  wg_commit();
  if (H > 0 && H < 13) wg_wait<1>();
  if (H >= 2 && H <= 8 && !(H & 1)) warp_arrive(sb + SM_MISC + B_FREEA + 8 * ((I + 2) % 3), lane);
}

__device__ __forceinline__ void proj_phase(const Params& p, uint32_t sb, int tid, int warp) {
  const int b = blockIdx.x, tb = b >> 2, cg = b & 3, lane = tid & 31, g = lane >> 2, t = lane & 3;
  const bool odd = cg & 1;
  float aq[56], ak[8];
  mbar_wait(sb + SM_MISC + B_B2, 0);
  uint32_t a0[2][4], a1[2][4];
  const uint32_t arow = (16 * warp + (lane & 15)) * 128, asw = ((lane >> 4) ^ (lane & 7)) << 4;
#define PH(H) proj_half<H>(aq, ak, a0, sb, arow, asw, lane); proj_half<H + 1>(aq, ak, a1, sb, arow, asw, lane);
  PH(0) PH(2) PH(4) PH(6) PH(8) PH(10)
  proj_half<12>(aq, ak, a0, sb, arow, asw, lane);
  proj_half<13>(aq, ak, a1, sb, arow, asw, lane);
#undef PH
  wg_wait<0>();
  pin(aq); pin(ak);
  TS(3);
  wg_bar(3);
  {
    const float sc = cg < 2 ? 0.2726437354213113f : 1.0f;
    const bool pad = odd && t >= 2;
    uint32_t stat = 0;
#pragma unroll
    for (int h = 0; h < 2; h++) {
      const int tok = tb * 64 + warp * 16 + g + 8 * h, r = tok & 127;
      const uint32_t w0 = pk_bf(ak[2 * h] * sc, ak[2 * h + 1] * sc);
      uint32_t w1 = pad ? 0u : pk_bf(ak[4 + 2 * h] * sc, ak[5 + 2 * h] * sc);
      if (cg == 1 && t == 2) p.g->gate[tok] = (uint16_t)pk_bf(__fdividef(1.0f, 1.0f + __expf(-bf_lo(pk_bf(ak[4 + 2 * h], 0.f)))), 0.f);
      const float x0 = bf_lo(w0), x1 = bf_hi(w0), x2 = bf_lo(w1), x3 = bf_hi(w1);
      float s = fmaf(x0, x0, fmaf(x1, x1, fmaf(x2, x2, x3 * x3)));
      s += __shfl_xor_sync(0xffffffffu, s, 1);
      s += __shfl_xor_sync(0xffffffffu, s, 2);
      stat = max(stat, __float_as_uint(s));
      if (pad) {
        const bool emu = (EMU_MASK >> (r >> 3)) & 1;
        w1 = cg == 1 ? (emu ? (t == 2 ? 0x3F803F80u : 0x00003F80u) : 0u) : (t == 2 ? 0x00003F80u : 0u);
      }
      const uint32_t row = sb + SM_RING + 16384 + (tok & 63) * 32 + t * 4;
      const int sw = (r >> 1) & 1;
      sts32(row + sw * 16, w0);
      sts32(row + (sw ^ 1) * 16, w1);
    }
    stat = __reduce_max_sync(0xffffffffu, stat);
    if (lane == 0) p.g->norm[cg * 128 + tb * 4 + warp] = __uint_as_float(stat);
  }
  wg_bar(3);
  {
    const int tok = tb * 64 + (tid >> 1), r = tok & 127;
    const uint4 kv = lds128(sb + SM_RING + 16384 + tid * 16);
    *reinterpret_cast<uint4*>(p.g->KV + (tok >> 7) * 4096 + (cg >> 1) * 2048 + r * 16 + (((r >> 2) ^ cg) & 1) * 8 + (tid & 1) * 4) = kv;
  }
  warp_arrive(sb + SM_MISC + B_SQKV, lane);
  {
    const uint32_t qb = sb + SM_RING + (warp >> 1) * 8192 + ((warp & 1) * 16 + g) * 64, sw = (g >> 1) << 4;
    const uint32_t pe = qb + t * 4, po = qb + 2048 + ((t + 2) & 3) * 4, up = t >= 2 ? 16 : 0;
    const uint32_t padw = t == 2 ? 0xBF8043C0u : 0x00003BEBu;
    uint32_t ad[7];
#pragma unroll
    for (int jj = 0; jj < 7; jj++)
      ad[jj] = jj < 3 ? pe + ((jj * 16) ^ sw) : jj == 3 ? (t < 2 ? pe + (48 ^ sw) : po + sw) : po + (((jj - 4) * 16 + up) ^ sw);
#pragma unroll
    for (int hp = 0; hp < 2; hp++) {
#pragma unroll
      for (int jj = 0; jj < 7; jj++) {
        const int j = 7 * hp + jj;
        sts32(ad[jj] + hp * 4096, pk_bf(aq[4 * j], aq[4 * j + 1]));
        sts32(ad[jj] + hp * 4096 + 512, pk_bf(aq[4 * j + 2], aq[4 * j + 3]));
      }
    }
    if (t >= 2) {
#pragma unroll
      for (int i = 0; i < 8; i++) sts32(pe + (48 ^ sw) + (i >> 1) * 2048 + (i & 1) * 512, padw);
    }
  }
  fence_async();
  warp_arrive(sb + SM_MISC + B_SQ, lane);
}

__device__ __forceinline__ void out_phase(const Params& p, uint32_t sb, const float (&o)[16]) {
  uint32_t tx;
  asm volatile("mov.u32 %0, %%tid.x;" : "=r"(tx));
  const uint32_t mb = sb + SM_MISC;
  const int b = blockIdx.x, rank = b & 1, wg = __shfl_sync(0xffffffffu, tx >> 7, 0), warp = __shfl_sync(0xffffffffu, (tx >> 5) & 3, 0);
  const int lane = tx & 31, g = lane >> 2, t = lane & 3;
    {
      const float i0 = __fdividef(1.0f, __shfl_sync(0xffffffffu, o[12], (lane & 28) | 2));
      const float i1 = __fdividef(1.0f, __shfl_sync(0xffffffffu, o[14], (lane & 28) | 2));
      const int k0 = 28 * (2 * wg + (warp >> 1)) + 2 * t;
      const uint32_t a = sb + SM_O + (k0 >> 3) * 512 + (8 * (g >> 1) + 4 * (warp & 1) + (g & 1)) * 16 + (k0 & 7) * 2;
#pragma unroll
      for (int j = 0; j < 4; j++) {
        if (j < 3 || t < 2) {
          sts32(a + j * 512, pk_bf(o[4 * j] * i0, o[4 * j + 1] * i0));
          sts32(a + j * 512 + 32, pk_bf(o[4 * j + 2] * i1, o[4 * j + 3] * i1));
        }
      }
    }
    fence_async();
    warp_arrive(mb + B_OW + 8 * wg, lane);
    if (lane == 0) mbar_arrive(mb + B_OST);
    const int tok0 = 32 * (b >> 1), col0 = (wg == 3 ? 192 + 32 * rank : 64 * (wg + 4 * rank)) + 16 * warp;
    const bool keeper = wg < 3 || warp < 2;
    uint4 b0v, b1v, gvv;
    const bool early = __shfl_sync(0xffffffffu, (int)mbar_test(mb + B_YRDY, 0), 0);
    if (keeper && early) {
      b0v = ldcg128(p.g->bT + (col0 + g) * SEQ + tok0 + 8 * t);
      b1v = ldcg128(p.g->bT + (col0 + g + 8) * SEQ + tok0 + 8 * t);
      gvv = ldcg128(p.g->gate + tok0 + 8 * t);
    }
    mbar_wait(mb + B_WO0, 0);
    mbar_wait(mb + B_OST, 0);
    TS(9);
    float acc[16];
    const uint32_t box = sb + SM_WO + wg * BOX;
    const uint32_t box2 = wg == 3 ? box + 14336 : sb + (wg == 0 ? SM_WO4 : SM_RING + (wg - 1) * BOX);
    const uint32_t sbo = wg == 3 ? 512 : 1024, swz = wg == 3 ? 2 : 1, kstep = sbo >> 3;
    {
      const uint64_t da = mkdesc(box, 0, sbo, swz), db = mkdesc(sb + SM_O, 512, 128, 0);
      wg_fence();
#pragma unroll
      for (int k = 0; k < 14; k++) mma_out32(acc, da + kstep * k, db + 64 * k, k);
      wg_commit();
    }
    mbar_wait_cluster(mb + B_ORECV, 0);
    if (wg < 3) mbar_wait(mb + (wg == 0 ? B_WO4 : B_WO0 + 8 * wg), 0);
    {
      const uint64_t da = mkdesc(box2, 0, sbo, swz), db = mkdesc(sb + SM_O + 14336, 512, 128, 0);
      wg_fence();
#pragma unroll
      for (int k = 0; k < 14; k++) mma_out32(acc, da + kstep * k, db + 64 * k, 1);
      wg_commit();
    }
    if (keeper && !early) {
      mbar_wait(mb + B_YRDY, 0);
      b0v = ldcg128(p.g->bT + (col0 + g) * SEQ + tok0 + 8 * t);
      b1v = ldcg128(p.g->bT + (col0 + g + 8) * SEQ + tok0 + 8 * t);
      gvv = ldcg128(p.g->gate + tok0 + 8 * t);
    }
    wg_wait<0>();
    pin(acc);
    wg_bar(wg);
    TS(10);
    if (keeper) {
      const uint32_t bv[8] = {b0v.x, b1v.x, b0v.y, b1v.y, b0v.z, b1v.z, b0v.w, b1v.w}, gv[4] = {gvv.x, gvv.y, gvv.z, gvv.w};
      uint32_t r[8];
#pragma unroll
      for (int j = 0; j < 4; j++) {
        const uint32_t om = bf2_sub(0x3F803F80u, gv[j]);
#pragma unroll
        for (int h = 0; h < 2; h++)
          r[2 * j + h] = bf2_add(bf2_mul(gv[j], pk_bf(acc[4 * j + 2 * h], acc[4 * j + 2 * h + 1])), bf2_mul(om, bv[2 * j + h]));
      }
      const uint32_t stage = box + 8192 + warp * 1024;
      const int m = lane >> 3;
#pragma unroll
      for (int s = 0; s < 2; s++)
        stsm4t(stage + (8 * (lane >> 1 & 3) + 4 * s + 2 * (m >> 1) + (lane & 1)) * 32 + (m & 1) * 16, r[4 * s], r[4 * s + 1], r[4 * s + 2], r[4 * s + 3]);
      __syncwarp();
#pragma unroll
      for (int s = 0; s < 2; s++) {
        const uint4 v = lds128(stage + s * 512 + lane * 16);
        *reinterpret_cast<uint4*>(p.out + (tok0 + 16 * s + (lane >> 1)) * DM + col0 + (lane & 1) * 8) = v;
      }
    }
}

__device__ __forceinline__ void wo_pieces(uint32_t sb, const CUtensorMap* two32, int rank, int u0, int u1) {
#pragma unroll 1
  for (int u = u0; u < u1; u++) {
    const int w = u < 7 ? 1 : u < 14 ? 2 : 0, r = u - (u < 7 ? 0 : u < 14 ? 7 : 14);
    tma2d(sb + SM_RING + u * 4096, two32, 64 * (4 * rank + w), 224 * (rank ^ 1) + 32 * r, sb + SM_MISC + (w == 0 ? B_WO4 : B_WO0 + 8 * w));
  }
}

__device__ __forceinline__ void helper_loader(const Params& p, uint32_t sb, const CUtensorMap* tx, const CUtensorMap* twq, const CUtensorMap* two,
                                              const CUtensorMap* two32, const CUtensorMap* twoh, const CUtensorMap* twq48) {
  const uint32_t mb = sb + SM_MISC;
  const int b = blockIdx.x, rank = b & 1;
  const unsigned ep = ldcg32(p.g->epoch + b) + 1;
  if (ep == 0) __nanosleep(1);
  mbar_expect(mb + B_XA, 24576);
#pragma unroll
  for (int i = 0; i < 3; i++) tma2d(sb + SM_RING + i * 24576, tx, qkv_chunk(b & 3, i) * 64, (b >> 2) * 64, mb + B_XA);
#pragma unroll 1
  for (int i = 0; i < 7; i++) {
    if (i >= 3) mbar_wait(mb + B_FREEA + 8 * (i == 6 ? 0 : i - 3), i == 6);
    qkv_issue(sb, tx, twq, twq48, i, b);
  }
  mbar_expect(mb + B_WO0, 4 * BOX); mbar_expect(mb + B_WOA, BOX); mbar_expect(mb + B_WOB, BOX); mbar_expect(mb + B_WO4, BOX);
  mbar_expect(mb + B_ORECV, 14336);
  poll(p.g->cnt + C_QKV, ep * N_QKV);
  TL(23);
  asm volatile("fence.proxy.async.global;" ::: "memory");
  mbar_wait(mb + B_QSENT, 0);
  mbar_expect(mb + B_QRDY, 2048);
  bulk_g2s(mb + M_NORM, p.g->norm, 2048, mb + B_QRDY);
#pragma unroll 1
  for (int j = -4; j < 16; j++) {
    if (j >= 0) mbar_wait(mb + B_EMPTY + 8 * (j & 3), (j >> 2) & 1);
    if (j < 12) {
      const uint32_t bar = mb + B_FULLKV + 8 * (j & 3);
      mbar_expect(bar, 16384);
      bulk_g2s(sb + SM_RING + (j & 3) * 16384, p.g->KV + (j + 4) * 4096, 16384, bar);
      if (j == 0) mbar_arrive_remote(mapa(mb + B_PEER, rank ^ 1));
      if (j >= 0 && j < 3) tma2d(sb + SM_WO + j * BOX, two, 64 * (j + 4 * rank), 224 * rank, mb + B_WO0);
      if (j == 3) {
        tma2d(sb + SM_WO + 3 * BOX, twoh, 192 + 32 * rank, 224 * rank, mb + B_WO0);
        tma2d(sb + SM_WO + 3 * BOX + 14336, twoh, 192 + 32 * rank, 224 * (rank ^ 1), mb + B_WO0);
      }
      if (j == 4) wo_pieces(sb, two32, rank, 20, 21);
    } else {
      wo_pieces(sb, two32, rank, 4 * j - 48, j == 15 ? 20 : 4 * j - 44);
    }
  }
  p.g->epoch[b] = ep;
}

__device__ __forceinline__ void helper_weights(const Params& p, uint32_t sb, int lane) {
  const int cg = blockIdx.x & 3, k0 = (112 * cg) & ~63, piece = lane & 3;
  const bool odd = cg & 1;
  const uint16_t* w = (cg < 2 ? p.wk : p.wv) + (odd ? 16 : 0) + (lane >> 2) * 28 + piece * 4;
  const uint32_t dst = sb + SM_B2 + (piece >> 1) * 128 + (lane >> 2) * 16 + (piece & 1) * 8;
  if (!(odd && piece == 3)) {
#pragma unroll 4
    for (int kg = 0; kg < 56; kg++) {
      const int k = 8 * kg + k0;
      asm volatile("cp.async.ca.shared.global [%0], [%1], 8;" ::"r"(dst + kg * 256), "l"(w + (k >= DM ? k - DM : k) * 28) : "memory");
    }
  }
  if (odd) {
#pragma unroll
    for (int h = 0; h < 2; h++) {
      uint32_t v[7];
#pragma unroll
      for (int i = 0; i < 7; i++) { const int k = lane + 32 * (7 * h + i) + k0; v[i] = __ldg(p.gw + (k >= DM ? k - DM : k)); }
#pragma unroll
      for (int i = 0; i < 7; i++) sts64(sb + SM_B2 + ((lane >> 3) + 4 * (7 * h + i)) * 256 + 136 + (lane & 7) * 16, v[i], 0u);
    }
  }
  asm volatile("cp.async.wait_all;" ::: "memory");
  fence_async();
  __syncwarp();
}

__device__ __forceinline__ void helper_publisher(const Params& p, uint32_t sb) {
  const uint32_t mb = sb + SM_MISC;
  const int b = blockIdx.x, rank = b & 1;
  mbar_wait(mb + B_SXT, 0);
  TL(24);
  publish(p.g->cnt + C_XT);
  TL(25);
  mbar_wait(mb + B_SQKV, 0);
  TL(26);
  publish(p.g->cnt + C_QKV);
  TL(27);
  mbar_wait(mb + B_SY, 0);
  publish(p.g->cnt + C_Y);
  mbar_wait(mb + B_PEER, 0);
#pragma unroll 1
  for (int w = 3; w >= 0; w--) {
    mbar_wait(mb + B_OW + 8 * w, 0);
    asm volatile("cp.async.bulk.shared::cluster.shared::cta.mbarrier::complete_tx::bytes [%0], [%1], 3584, [%2];" ::"r"(mapa(sb + SM_O + 14336 + w * 3584, rank ^ 1)),
                 "r"(sb + SM_O + w * 3584), "r"(mapa(mb + B_ORECV, rank ^ 1)) : "memory");
  }
  mbar_wait(mb + B_ORECV, 0);
  mbar_arrive_remote(mapa(mb + B_DONE, rank ^ 1));
  mbar_wait(mb + B_DONE, 0);
}

__device__ __forceinline__ void helper_poller(const Params& p, uint32_t sb) {
  const uint32_t mb = sb + SM_MISC;
  const int b = blockIdx.x;
  const unsigned ep = ldcg32(p.g->epoch + b) + 1;
  poll(p.g->cnt + C_XT, ep * N_XT);
  TL(28);
  asm volatile("fence.proxy.async.global;" ::: "memory");
#pragma unroll 1
  for (int w = 0; w < 3; w++) load_u(p, 3 * b + w, sb + SM_U + w * U_SIZE, mb + B_U + 8 * w);
  mbar_wait(mb + B_SQ, 0);
  {
    uint32_t* dst = p.g->Q + (((b >> 2) * 4 + (b >> 1 & 1)) * 4 + (b & 1) * 2) * 1024;
    asm volatile("cp.async.bulk.global.shared::cta.bulk_group [%0], [%1], 8192;" ::"l"(dst), "r"(sb + SM_RING) : "memory");
    asm volatile("cp.async.bulk.global.shared::cta.bulk_group [%0], [%1], 8192;" ::"l"(dst + 8192), "r"(sb + SM_RING + 8192) : "memory");
    asm volatile("cp.async.bulk.commit_group;\ncp.async.bulk.wait_group 0;" ::: "memory");
    mbar_arrive(mb + B_QSENT);
    asm volatile("fence.proxy.async.global;" ::: "memory");
  }
  publish(p.g->cnt + C_Q + (b >> 2) * 8);
  poll(p.g->cnt + C_Q + (b >> 2) * 8, ep * N_Q);
  TL(22);
  asm volatile("fence.proxy.async.global;" ::: "memory");
  mbar_expect(mb + B_QRDY, 16384);
  bulk_g2s(sb + SM_QS, p.g->Q + b * 4096, 16384, mb + B_QRDY);
  poll(p.g->cnt + C_Y, ep * N_Y);
  TL(29);
  mbar_arrive(mb + B_YRDY);
}

__device__ __forceinline__ void helper_extra(const Params& p, uint32_t sb, int lane) {
  const uint32_t mb = sb + SM_MISC;
  const int b = blockIdx.x;
  const unsigned ep = ldcg32(p.g->epoch + b) + 1;
  if (lane == 0) {
    poll(p.g->cnt + C_XT, ep * N_XT);
    asm volatile("fence.proxy.async.global;" ::: "memory");
#pragma unroll 1
    for (int w = 0; w < 4; w++) load_u(p, 384 + 4 * (b - NMAIN) + w, sb + SM_RING + 2 * w * U_SIZE, mb + B_U + 8 * w);
  }
  if (lane < 12) poll(p.g->cnt + C_KP + (16 * (lane >> 2) + 4 * (b - NMAIN) + (lane & 3)) * 8, ep * N_KP);
  __syncwarp();
  if (lane == 0) { mbar_arrive(mb + B_YRDY); p.g->epoch[b] = ep; }
}

__global__ void __cluster_dims__(2, 1, 1) __launch_bounds__(640, 1)
fused_kernel(const __grid_constant__ Params p, const __grid_constant__ CUtensorMap tx, const __grid_constant__ CUtensorMap twq,
             const __grid_constant__ CUtensorMap two, const __grid_constant__ CUtensorMap two32, const __grid_constant__ CUtensorMap twoh,
             const __grid_constant__ CUtensorMap twq48) {
  extern __shared__ __align__(1024) unsigned char smem[];
  const int b = blockIdx.x, rank = b & 1, tid = threadIdx.x & 127;
  const bool is_main = b < NMAIN;
  uint32_t raw[6], ldt = 0;
  {
    const int w = threadIdx.x >> 7;
    const bool pj = is_main && w == 3;
    const int c = is_main ? (pj ? CH_HAND + (b >> 1) : 3 * b + w) : 384 + 4 * (b - NMAIN) + w;
    const uint16_t* src[6] = {p.are, p.aim, p.bre, p.bim, p.cre, p.cim};
    if (w < 4 && !pj) {
#pragma unroll
      for (int k = 0; k < 6; k++) raw[k] = __ldg(reinterpret_cast<const uint32_t*>(src[k] + c * NST + 2 * tid));
    } else if (pj && b < 2 * NHAND) {
#pragma unroll
      for (int k = 0; k < 6; k++) raw[k] = __ldg(src[k] + c * NST + 128 * rank + tid);
    }
    if (w < 4) ldt = __ldg(p.ldt + min(c, DM - 1));
  }
  const uint32_t sb = __shfl_sync(0xffffffffu, (uint32_t)__cvta_generic_to_shared(smem), 0);
  const uint32_t mb = sb + SM_MISC;
  const int wg = __shfl_sync(0xffffffffu, threadIdx.x >> 7, 0);
  const int warp = __shfl_sync(0xffffffffu, tid >> 5, 0), lane = tid & 31;

  if (wg == 4) {
    asm volatile("setmaxnreg.dec.sync.aligned.u32 32;");
    if (warp == 0) {
      if (elect_one()) {
#pragma unroll
        for (uint32_t o = 0; o <= B_X2 + 16; o += 8) mbar_init(mb + o, o == B_QRDY ? 2 : (o < B_QRDY || o == B_B2) ? 1 : (o < B_SY || o > B_B2) ? 4 : o == B_SY ? 12 : 16);
        asm volatile("fence.mbarrier_init.release.cluster;" ::: "memory");
        fence_async();
      }
      __syncwarp();
      asm volatile("bar.arrive 5, 160;\nbar.arrive 6, 160;\nbar.arrive 7, 160;\nbar.arrive 8, 160;\nbar.arrive 9, 96;\nbar.arrive 10, 64;" ::: "memory");
      if (is_main) { if (elect_one()) helper_loader(p, sb, &tx, &twq, &two, &two32, &twoh, &twq48); }
      else helper_extra(p, sb, lane);
    } else {
      if (warp == 3) {
        if (is_main) helper_weights(p, sb, lane);
        asm volatile("bar.sync 10, 64;" ::: "memory");
      } else {
        asm volatile("bar.sync 9, 96;" ::: "memory");
      }
      if (is_main && elect_one()) {
        if (warp == 1) helper_publisher(p, sb);
        else if (warp == 2) helper_poller(p, sb);
        else {
          mbar_arrive(mb + B_B2);
          if (b < 2 * NHAND) {
            mbar_wait(mb + B_SKP, 0);
            publish(p.g->cnt + C_KP + (b >> 1) * 8);
          }
        }
      }
    }
  } else {
    const int t = lane & 3;
    const bool proj = is_main && wg == 3;
    TS(0);
    int ch = is_main ? 3 * b + wg : 384 + 4 * (b - NMAIN) + wg;
    const bool has_ssm = !proj || b < 2 * NHAND;
    asm volatile("setmaxnreg.inc.sync.aligned.u32 112;");
    const uint32_t stg = sb + SM_STG + wg * BOX;

    const uint32_t wbase = stg + warp * 7168;
    float dt = 0.f, isc = 0.f;
    C2 cb1 = {0.f, 0.f};
    if (has_ssm) {
      dt = bf_lo(pk_bf(expf(bf_lo(ldt)), 0.f));
      const C2 cb0 = cmul(C2{bf_lo(raw[4]), bf_lo(raw[5])}, C2{bf_lo(raw[2]) * dt, bf_lo(raw[3]) * dt});
      cb1 = cmul(C2{bf_hi(raw[4]), bf_hi(raw[5])}, C2{bf_hi(raw[2]) * dt, bf_hi(raw[3]) * dt});
      const float mx = fmaxf(fmaxf(fabsf(cb0.r), fabsf(cb0.i)), fmaxf(fabsf(cb1.r), fabsf(cb1.i)));
      uint32_t e = __reduce_max_sync(0xffffffffu, __float_as_uint(mx)) >> 23;
      e = min(max(e, 14u), 254u);
      const float sc = __uint_as_float((267u - e) << 23);
      isc = __uint_as_float((e - 13u) << 23);
      cb1 = C2{cb1.r * sc, -cb1.i * sc};
      kgen_rows(wbase, lane, kgen_base(raw[0], raw[1], dt), C2{cb0.r * sc, -cb0.i * sc});
    }
    if (proj) {
      asm volatile("bar.sync 8, 160;" ::: "memory");
      if (has_ssm) {
        if (lane == 0) stsf(mb + M_ISC + 4 * warp, isc);
        warp_arrive(mb + B_GEN, lane);
      }
      proj_transpose(p, sb, tid, warp);
      TS(15);
      proj_phase(p, sb, tid, warp);
      TS(4);
#pragma unroll 1
      for (int w = 0; w < 3; w++) {
        mbar_wait(mb + B_T3 + 8 * w, 0);
        mbar_wait(mb + B_U + 8 * w, 0);
        far_sums(sb + SM_STG + w * BOX + ST_B3, sb + SM_U + w * U_SIZE, tid);
        fence_async();
        warp_arrive(mb + B_X2 + 8 * w, lane);
      }
    } else {
      ChanIn in;
      uint32_t ut = sb + (is_main ? SM_U + wg * U_SIZE : SM_RING + 2 * wg * U_SIZE), ut_next = ut + U_SIZE;
      if (tid < (is_main ? 32 : 64)) sts128(ut + (tid >> 5) * U_SIZE + (tid & 3) * U_LBO + (64 + (tid >> 2 & 7)) * 16, 0u, 0u, 0u, 0u);
      fence_async();
      in.dskip = bf_lo(__ldg(p.dsk + ch));
      asm volatile("bar.sync %0, 160;" ::"r"(5 + wg) : "memory");
      {
        float acc[2][3][4];
#pragma unroll
        for (int i = 0; i < 24; i++) (&acc[0][0][0])[i] = 0.f;
        const KgBase k1 = kgen_base(raw[0] >> 16, raw[1] >> 16, dt);
        kgen_mma(wbase, lane, acc);
        __syncwarp();
        kgen_rows(wbase, lane, k1, cb1);
        if (b < 2 * NHAND && (warp & 1) == wg) {
          mbar_wait(mb + B_GEN, 0);
          const uint32_t hb = sb + SM_STG + 3 * BOX + warp * 7168;
          float hacc[2][3][4];
#pragma unroll
          for (int i = 0; i < 24; i++) (&hacc[0][0][0])[i] = 0.f;
          kgen_mma(hb, lane, hacc);
          kgen_store(hb, warp, lane, hacc, ldsf(mb + M_ISC + 4 * warp));
          warp_arrive(mb + B_PART, lane);
        }
        kgen_mma(wbase, lane, acc);
        kgen_store(wbase, warp, lane, acc, isc);
      }
      TS(12);
      {
        wg_bar(wg);
#pragma unroll
        for (int q = 0; q < 8; q++) {
          in.gw[q] = 0.f;
          if (q < 2 || !(q & 1)) in.gv[q] = ksum(stg, kidx(tid, q));
        }
        {
          const float edge = lane < 3 ? ksum(stg, kidx(tid | 31, 3 + 2 * lane)) : 0.f;
#pragma unroll
          for (int q = 3; q < 8; q += 2) {
            const float up = __shfl_down_sync(0xffffffffu, in.gv[q - 1], 1), last = __shfl_sync(0xffffffffu, edge, q >> 1 ? (q - 3) >> 1 : 0);
            in.gv[q] = lane == 31 ? last : up;
          }
        }
        if (b < 2 * NHAND && wg == 2) {
          mbar_wait(mb + B_PART, 0);
          float* kp = p.g->Kp + b * KP_STRIDE;
#pragma unroll
          for (int q = 0; q < 5; q++) kp[tid + 128 * q] = ksum(stg + BOX, tid + 128 * q);
          if (tid == 0) kp[640] = ksum(stg + BOX, 640);
          warp_arrive(mb + B_SKP, lane);
        }
        int upar = 0;
#pragma unroll 1
        for (;;) {
          const int next = (is_main || ch >= DM - 16) ? -1 : ch + 16;
          conv_channel(p, stg, ut, ut_next, mb + B_U + 8 * wg, upar, wg, tid, ch, in, next, mb + B_YRDY, is_main ? mb : 0u);
          if (!is_main) TS(8 + ((ch - 384) >> 4));
          if (next < 0) break;
          ch = next;
          upar ^= 1;
          const uint32_t tmp = ut; ut = ut_next; ut_next = tmp;
        }
        if (is_main) warp_arrive(mb + B_SY, lane);
      }
    }
    if (!is_main) {
      wg_bar(wg);
      if (tid == 0) publish(p.g->cnt + C_Y);
      TDUMP();
      return;
    }
    TS(6);

    float o[16];
    {
      mbar_wait(mb + B_QRDY, 0);
      uint32_t q[8];
      {
        const int row = 16 * warp + (lane & 15);
        const uint32_t qa = sb + SM_QS + wg * 4096 + row * 64, sw = (row >> 1) & 3;
        uint32_t lo[4], hi[4];
        ldsm4(lo, qa + (((lane >> 4) ^ sw) << 4));
        ldsm4(hi, qa + (((2 + (lane >> 4)) ^ sw) << 4));
#pragma unroll
        for (int r = 0; r < 4; r++) { q[r] = lo[r]; q[4 + r] = (r >= 2 && t >= 2) ? 0u : hi[r]; }
      }
      float thr;
      {
        uint32_t st[4];
#pragma unroll
        for (int a = 0; a < 4; a++) {
          const uint4 v = lds128(mb + M_NORM + a * 512 + lane * 16);
          st[a] = __reduce_max_sync(0xffffffffu, max(max(v.x, v.y), max(v.z, v.w)));
        }
        const float k2 = __uint_as_float(st[0]) + __uint_as_float(st[1]), v2 = __uint_as_float(max(st[2], st[3]));
        const bool vok = v2 >= 3.7252903e-09f && v2 <= 4.2949673e+09f;
        thr = vok ? __fdividef(SCORE_BOUND * SCORE_BOUND * 0.9f, k2) : -1.f;
      }
      const uint32_t s0 = bf2_fma(q[6], q[6], bf2_fma(q[4], q[4], bf2_fma(q[2], q[2], bf2_mul(q[0], q[0]))));
      const uint32_t s1 = bf2_fma(q[7], q[7], bf2_fma(q[5], q[5], bf2_fma(q[3], q[3], bf2_mul(q[1], q[1]))));
      float n0 = bf_lo(s0) + bf_hi(s0), n1 = bf_lo(s1) + bf_hi(s1);
      n0 += __shfl_xor_sync(0xffffffffu, n0, 1); n0 += __shfl_xor_sync(0xffffffffu, n0, 2);
      n1 += __shfl_xor_sync(0xffffffffu, n1, 1); n1 += __shfl_xor_sync(0xffffffffu, n1, 2);
      uint32_t unsafe = !(n0 <= thr && n1 <= thr);
      asm volatile("{\n.reg .pred p, q;\nsetp.ne.b32 p, %0, 0;\nbarrier.red.or.pred q, %1, 128, p;\nselp.b32 %0, 1, 0, q;\n}" : "+r"(unsafe) : "r"(wg + 1) : "memory");
      unsafe = __shfl_sync(0xffffffffu, unsafe, 0);
#pragma unroll
      for (int i = 0; i < 16; i++) o[i] = 0.f;
      pin(o);
      TS(7);
      if (unsafe) attn_safe(o, q, sb, lane);
      else attn_fast(o, sb, wg, lane);
    }
    TS(8);

    out_phase(p, sb, o);
    TS(11); __syncwarp(); TDUMP();
  }
}

typedef CUresult (*EncodeFn)(CUtensorMap*, CUtensorMapDataType, cuuint32_t, void*, const cuuint64_t*, const cuuint64_t*, const cuuint32_t*,
                             const cuuint32_t*, CUtensorMapInterleave, CUtensorMapSwizzle, CUtensorMapL2promotion, CUtensorMapFloatOOBfill);

void encode2d(EncodeFn fn, CUtensorMap* tm, const void* ptr, int rows, int box_rows, int box_cols = 64) {
  cuuint64_t dims[2] = {(cuuint64_t)DM, (cuuint64_t)rows}, strides[1] = {(cuuint64_t)DM * 2};
  cuuint32_t box[2] = {(cuuint32_t)box_cols, (cuuint32_t)box_rows}, es[2] = {1, 1};
  fn(tm, CU_TENSOR_MAP_DATA_TYPE_BFLOAT16, 2, const_cast<void*>(ptr), dims, strides, box, es, CU_TENSOR_MAP_INTERLEAVE_NONE,
     box_cols > 32 ? CU_TENSOR_MAP_SWIZZLE_128B : CU_TENSOR_MAP_SWIZZLE_64B, CU_TENSOR_MAP_L2_PROMOTION_L2_128B, CU_TENSOR_MAP_FLOAT_OOB_FILL_NONE);
}

}

extern "C" void kernel_launch(void* const* d_in, const int* in_sizes, int n_in, void* d_out, int out_size) {
  static EncodeFn enc = nullptr;
  static void* scratch = nullptr;
  if (!enc) {
    void* fn = nullptr;
    cudaDriverEntryPointQueryResult qr;
    cudaGetDriverEntryPoint("cuTensorMapEncodeTiled", &fn, cudaEnableDefault, &qr);
    enc = (EncodeFn)fn;
    cudaGetSymbolAddress(&scratch, gs_);
    cudaFuncSetAttribute(fused_kernel, cudaFuncAttributeMaxDynamicSharedMemorySize, SM_TOTAL);
  }
  CUtensorMap tx, twq, two, two32, twoh, twq48;
  encode2d(enc, &tx, d_in[0], SEQ, 64);
  encode2d(enc, &twq, d_in[1], DM, 64);
  encode2d(enc, &two, d_in[4], DM, 224);
  encode2d(enc, &two32, d_in[4], DM, 32);
  encode2d(enc, &twoh, d_in[4], DM, 224, 32);
  encode2d(enc, &twq48, d_in[1], DM, 64, 48);
  Params p;
  p.wk = (const uint16_t*)d_in[2]; p.wv = (const uint16_t*)d_in[3];
  p.are = (const uint16_t*)d_in[6]; p.aim = (const uint16_t*)d_in[7];
  p.bre = (const uint16_t*)d_in[8]; p.bim = (const uint16_t*)d_in[9];
  p.cre = (const uint16_t*)d_in[10]; p.cim = (const uint16_t*)d_in[11];
  p.ldt = (const uint16_t*)d_in[12]; p.dsk = (const uint16_t*)d_in[13];
  p.gw = (const uint16_t*)d_in[14];
  p.out = (uint16_t*)d_out;
  p.g = (Scratch*)scratch;
  fused_kernel<<<NCTA, 640, SM_TOTAL>>>(p, tx, twq, two, two32, twoh, twq48);
}
```
